```python
import torch

def _softmax(x, axis=-1):
    return torch.softmax(x, dim=axis)
def _gelu(x):
    return torch.nn.functional.gelu(x, approximate="tanh")
def _silu(x):
    return torch.nn.functional.silu(x)
def _sigmoid(x):
    return torch.sigmoid(x)
def _layernorm(x, axis=-1, eps=1e-5):
    m = x.mean(dim=axis, keepdim=True)
    v = x.var(dim=axis, keepdim=True, unbiased=False)
    return (x - m) / torch.sqrt(v + eps)
def _scatter_add(tgt, idx, src, axis=0):
    return tgt.clone().index_add_(axis, idx, src)
def _segment_sum(src, seg, n):
    out = torch.zeros((n,) + src.shape[1:], dtype=src.dtype)
    return out.index_add_(0, seg, src)
def _pad(x, pw):
    flat = tuple(v for pair in reversed(pw) for v in pair)
    return torch.nn.functional.pad(x, flat)

kernel_name = 'interleave_layers__linear_attn_block__swiglu_ffn__prompt'

def setup_inputs():

    _w = (lambda a: (lambda t: t.to(torch.bfloat16) if t.is_floating_point() else t)(torch.as_tensor(a)))
    def _A_setup():
        B, S, D = 1, 2048, 1024
        return {
            "x": _w((lambda *s: torch.randn(*s, dtype=torch.bfloat16) * 0.05)(B, S, D)),
            "wqkv": _w((lambda *s: torch.randn(*s, dtype=torch.bfloat16) * 0.05)(D, 3 * D)),
            "wo": _w((lambda *s: torch.randn(*s, dtype=torch.bfloat16) * 0.05)(D, D)),
        }
    _A_in = _A_setup()

    def _B_setup():
        B, S, D, F = 1, 2048, 1024, 3584
        return {
            "x": _w((lambda *s: torch.randn(*s, dtype=torch.bfloat16) * 0.05)(B, S, D)),
            "w_gate": _w((lambda *s: torch.randn(*s, dtype=torch.bfloat16) * 0.05)(D, F)),
            "w_up": _w((lambda *s: torch.randn(*s, dtype=torch.bfloat16) * 0.05)(D, F)),
            "w_down": _w((lambda *s: torch.randn(*s, dtype=torch.bfloat16) * 0.05)(F, D)),
        }
    _B_in = _B_setup()

    return {
        "A_x": _A_in["x"],
        "A_wqkv": _A_in["wqkv"],
        "A_wo": _A_in["wo"],
        "B_x": _B_in["x"],
        "B_w_gate": _B_in["w_gate"],
        "B_w_up": _B_in["w_up"],
        "B_w_down": _B_in["w_down"],
    }

def reference(A_x, A_wqkv, A_wo, B_x, B_w_gate, B_w_up, B_w_down):
    def _A_ref(x, wqkv, wo):
        B, S, D = x.shape
        H = 32; Dh = D // H
        qkv = (lambda x, *d: x.permute(*d))((x @ wqkv).reshape(B, S, 3, H, Dh), 2, 0, 3, 1, 4)
        q, k, v = qkv[0], qkv[1], qkv[2]
        phi = lambda t: torch.where(t > 0, t + 1, torch.exp(t)) + 1e-6
        pq, pk = phi(q), phi(k)
        kv = torch.einsum("bhsd,bhse->bhde", pk, v)
        z = torch.einsum("bhsd->bhd", pk)
        num = torch.einsum("bhqd,bhde->bhqe", pq, kv)
        den = torch.einsum("bhqd,bhd->bhq", pq, z)[..., None] + 1e-6
        o = num / den
        return (lambda x, *d: x.permute(*d))(o, 0, 2, 1, 3).reshape(B, S, D) @ wo

    def _B_ref(x, w_gate, w_up, w_down):
        g = _silu(x @ w_gate)
        u = x @ w_up
        return (g * u) @ w_down

    x = A_x
    x = x + _A_ref(_layernorm(x, axis=-1), A_wqkv, A_wo)
    x = x + _B_ref(_layernorm(x, axis=-1), B_w_gate, B_w_up, B_w_down)
    x = x + _A_ref(_layernorm(x, axis=-1), A_wqkv, A_wo)
    x = x + _B_ref(_layernorm(x, axis=-1), B_w_gate, B_w_up, B_w_down)
    return x
```

```cpp
#include <cuda_runtime.h>
#include <cuda_bf16.h>
#include <cuda.h>
#include <stdint.h>

namespace {

constexpr int S_ = 2048, D_ = 1024, F_ = 3584;
constexpr int NSLOT = 12;
constexpr uint32_t SLOT = 16384;
constexpr uint32_t OFF_STG = NSLOT * SLOT;
constexpr uint32_t OFF_CSQ = OFF_STG + 32768;
constexpr uint32_t OFF_ONES = OFF_CSQ + 1536;
constexpr uint32_t OFF_BAR = OFF_ONES + 256;
constexpr uint32_t SMEM_BYTES = OFF_BAR + 512;
constexpr uint32_t OFF_CSGU = OFF_STG + 16384;

__device__ __align__(1024) uint8_t g_o[16 * 16 * SLOT];
__device__ __align__(1024) uint8_t g_x1[16 * 16 * SLOT];
__device__ __align__(1024) uint8_t g_x2[16 * 16 * SLOT];
__device__ __align__(1024) uint8_t g_h[16 * 56 * SLOT];
__device__ __align__(128) float2 g_stats[4][S_][8];
__device__ __align__(128) float g_cs[3072 + 2 * F_];
__device__ __align__(128) float g_kv[2][2][32][1056];
__device__ __align__(128) uint32_t g_flag[2][4][16][32];
__device__ __align__(128) uint32_t g_kvcnt[2][8][32];
__device__ uint32_t g_epoch;

struct Params {
  CUtensorMap x, wqkv_n, wqkv_p, wo_p, wg_p, wu_p, wd_p;
  const __nv_bfloat16* xin;
  __nv_bfloat16* out;
};

__device__ __forceinline__ uint32_t smem_u32(const void* p) { return (uint32_t)__cvta_generic_to_shared(p); }
__device__ __forceinline__ void mbar_init(uint32_t bar, uint32_t count) { asm volatile("mbarrier.init.shared::cta.b64 [%0], %1;" :: "r"(bar), "r"(count) : "memory"); }
__device__ __forceinline__ void mbar_expect_tx(uint32_t bar, uint32_t bytes) { asm volatile("mbarrier.arrive.expect_tx.shared::cta.b64 _, [%0], %1;" :: "r"(bar), "r"(bytes) : "memory"); }
__device__ __forceinline__ void mbar_arrive(uint32_t bar) { asm volatile("mbarrier.arrive.shared::cta.b64 _, [%0];" :: "r"(bar) : "memory"); }
__device__ __forceinline__ void mbar_arrive_cluster(uint32_t bar, uint32_t cta) {
  asm volatile("{\n.reg .b32 ra;\nmapa.shared::cluster.u32 ra, %0, %1;\nmbarrier.arrive.shared::cluster.b64 _, [ra];\n}\n" :: "r"(bar), "r"(cta) : "memory");
}
__device__ __forceinline__ bool mbar_try_wait(uint32_t bar, uint32_t parity) {
  uint32_t ok;
  asm volatile("{\n.reg .pred p;\nmbarrier.try_wait.parity.shared::cta.b64 p, [%1], %2;\nselp.u32 %0, 1, 0, p;\n}\n" : "=r"(ok) : "r"(bar), "r"(parity) : "memory");
  return ok;
}
__device__ __forceinline__ void mbar_wait(uint32_t bar, uint32_t parity) {
  if (mbar_try_wait(bar, parity)) return;
  uint32_t n = 0;
  while (!mbar_try_wait(bar, parity)) { if (++n > (1u << 20)) __trap(); }
}
__device__ __forceinline__ void tma_2d(uint32_t dst, const CUtensorMap* m, uint32_t bar, int c0, int c1) {
  asm volatile("cp.async.bulk.tensor.2d.shared::cluster.global.mbarrier::complete_tx::bytes [%0], [%1, {%3, %4}], [%2];"
    :: "r"(dst), "l"((uint64_t)m), "r"(bar), "r"(c0), "r"(c1) : "memory");
}
__device__ __forceinline__ void tma_5d_mc(uint32_t dst, const CUtensorMap* m, uint32_t bar, int c0, int c4) {
  asm volatile("cp.async.bulk.tensor.5d.shared::cluster.global.mbarrier::complete_tx::bytes.multicast::cluster [%0], [%1, {%3, %5, %5, %5, %4}], [%2], %6;"
    :: "r"(dst), "l"((uint64_t)m), "r"(bar), "r"(c0), "r"(c4), "r"(0), "h"((uint16_t)3) : "memory");
}
__device__ __forceinline__ void bulk_load(uint32_t dst, const void* src, uint32_t bytes, uint32_t bar) {
  asm volatile("cp.async.bulk.shared::cluster.global.mbarrier::complete_tx::bytes [%0], [%1], %2, [%3];"
    :: "r"(dst), "l"((uint64_t)src), "r"(bytes), "r"(bar) : "memory");
}
__device__ __forceinline__ void wgmma_fence() { asm volatile("wgmma.fence.sync.aligned;" ::: "memory"); }
__device__ __forceinline__ void wgmma_commit() { asm volatile("wgmma.commit_group.sync.aligned;" ::: "memory"); }
template<int N> __device__ __forceinline__ void wgmma_wait() { asm volatile("wgmma.wait_group.sync.aligned %0;" :: "n"(N) : "memory"); }
__device__ __forceinline__ void cluster_sync() { asm volatile("barrier.cluster.arrive.release.aligned;\nbarrier.cluster.wait.acquire.aligned;" ::: "memory"); }
__device__ __forceinline__ void fence_async_smem() { asm volatile("fence.proxy.async.shared::cta;" ::: "memory"); }
__device__ __forceinline__ void fence_async_global() { asm volatile("fence.proxy.async.global;" ::: "memory"); }
__device__ __forceinline__ void fence_gpu() { asm volatile("fence.acq_rel.gpu;" ::: "memory"); }
__device__ __forceinline__ void wg_bar(int id) { if (id == 1) asm volatile("bar.sync 1, 128;" ::: "memory"); else asm volatile("bar.sync 2, 128;" ::: "memory"); }
__device__ __forceinline__ uint32_t ld_acquire(const uint32_t* p) { uint32_t v; asm volatile("ld.acquire.gpu.global.u32 %0, [%1];" : "=r"(v) : "l"(p) : "memory"); return v; }
__device__ __forceinline__ void st_relaxed(uint32_t* p, uint32_t v) { asm volatile("st.relaxed.gpu.global.u32 [%0], %1;" :: "l"(p), "r"(v) : "memory"); }
__device__ __forceinline__ void red_add_u32(uint32_t* p, uint32_t v) { asm volatile("red.relaxed.gpu.global.add.u32 [%0], %1;" :: "l"(p), "r"(v) : "memory"); }
__device__ __forceinline__ void red_add_f32(float* p, float v) { asm volatile("red.relaxed.gpu.global.add.f32 [%0], %1;" :: "l"(p), "f"(v) : "memory"); }
__device__ __forceinline__ void red_add_v4(float* p, float a, float b, float c, float d) {
  asm volatile("red.relaxed.gpu.global.add.v4.f32 [%0], {%1, %2, %3, %4};" :: "l"(p), "f"(a), "f"(b), "f"(c), "f"(d) : "memory");
}
__device__ __forceinline__ void stmatrix_x4(uint32_t addr, uint32_t r0, uint32_t r1, uint32_t r2, uint32_t r3) {
  asm volatile("stmatrix.sync.aligned.m8n8.x4.shared.b16 [%0], {%1, %2, %3, %4};" :: "r"(addr), "r"(r0), "r"(r1), "r"(r2), "r"(r3) : "memory");
}
__device__ __forceinline__ float2 lds_f2(uint32_t addr) { float2 v; asm volatile("ld.shared.v2.f32 {%0, %1}, [%2];" : "=f"(v.x), "=f"(v.y) : "r"(addr)); return v; }
__device__ __forceinline__ void sts_u32(uint32_t addr, uint32_t v) { asm volatile("st.shared.u32 [%0], %1;" :: "r"(addr), "r"(v) : "memory"); }
__device__ __forceinline__ void sts_v4(uint32_t addr, uint4 v) { asm volatile("st.shared.v4.u32 [%0], {%1, %2, %3, %4};" :: "r"(addr), "r"(v.x), "r"(v.y), "r"(v.z), "r"(v.w) : "memory"); }
__device__ __forceinline__ uint32_t pack_bf16(float lo, float hi) { uint32_t r; asm("cvt.rn.bf16x2.f32 %0, %1, %2;" : "=r"(r) : "f"(hi), "f"(lo)); return r; }
__device__ __forceinline__ float bf_lo(uint32_t v) { return __uint_as_float(v << 16); }
__device__ __forceinline__ float bf_hi(uint32_t v) { return __uint_as_float(v & 0xffff0000u); }
__device__ __forceinline__ float ex2f(float x) { float r; asm("ex2.approx.ftz.f32 %0, %1;" : "=f"(r) : "f"(x)); return r; }
__device__ __forceinline__ float rcpf(float x) { float r; asm("rcp.approx.ftz.f32 %0, %1;" : "=f"(r) : "f"(x)); return r; }
__device__ __forceinline__ float phif(float t) { return (t > 0.f ? t + 1.f : ex2f(t * 1.4426950408889634f)) + 1e-6f; }
__device__ __forceinline__ uint64_t make_desc(uint32_t addr, uint32_t lbo, uint32_t sbo) {
  return (uint64_t)((addr & 0x3FFFF) >> 4) | ((uint64_t)(lbo >> 4) << 16) | ((uint64_t)(sbo >> 4) << 32) | (1ull << 62);
}
__device__ __forceinline__ unsigned long long gtime() { unsigned long long t; asm volatile("mov.u64 %0, %%globaltimer;" : "=l"(t)); return t; }

template<bool INIT> __device__ __forceinline__ void wgmma_n256_ss(float* d, uint64_t da, uint64_t db) {
  if constexpr (INIT) {
  asm volatile("{\n.reg .pred p;\nsetp.ne.b32 p, 0, 0;\nwgmma.mma_async.sync.aligned.m64n256k16.f32.bf16.bf16 {%0, %1, %2, %3, %4, %5, %6, %7, %8, %9, %10, %11, %12, %13, %14, %15, %16, %17, %18, %19, %20, %21, %22, %23, %24, %25, %26, %27, %28, %29, %30, %31, %32, %33, %34, %35, %36, %37, %38, %39, %40, %41, %42, %43, %44, %45, %46, %47, %48, %49, %50, %51, %52, %53, %54, %55, %56, %57, %58, %59, %60, %61, %62, %63, %64, %65, %66, %67, %68, %69, %70, %71, %72, %73, %74, %75, %76, %77, %78, %79, %80, %81, %82, %83, %84, %85, %86, %87, %88, %89, %90, %91, %92, %93, %94, %95, %96, %97, %98, %99, %100, %101, %102, %103, %104, %105, %106, %107, %108, %109, %110, %111, %112, %113, %114, %115, %116, %117, %118, %119, %120, %121, %122, %123, %124, %125, %126, %127}, %128, %129, p, 1, 1, 0, 1;\n}\n"
    : "=f"(d[0]), "=f"(d[1]), "=f"(d[2]), "=f"(d[3]), "=f"(d[4]), "=f"(d[5]), "=f"(d[6]), "=f"(d[7]), "=f"(d[8]), "=f"(d[9]), "=f"(d[10]), "=f"(d[11]), "=f"(d[12]), "=f"(d[13]), "=f"(d[14]), "=f"(d[15]), "=f"(d[16]), "=f"(d[17]), "=f"(d[18]), "=f"(d[19]), "=f"(d[20]), "=f"(d[21]), "=f"(d[22]), "=f"(d[23]), "=f"(d[24]), "=f"(d[25]), "=f"(d[26]), "=f"(d[27]), "=f"(d[28]), "=f"(d[29]), "=f"(d[30]), "=f"(d[31]), "=f"(d[32]), "=f"(d[33]), "=f"(d[34]), "=f"(d[35]), "=f"(d[36]), "=f"(d[37]), "=f"(d[38]), "=f"(d[39]), "=f"(d[40]), "=f"(d[41]), "=f"(d[42]), "=f"(d[43]), "=f"(d[44]), "=f"(d[45]), "=f"(d[46]), "=f"(d[47]), "=f"(d[48]), "=f"(d[49]), "=f"(d[50]), "=f"(d[51]), "=f"(d[52]), "=f"(d[53]), "=f"(d[54]), "=f"(d[55]), "=f"(d[56]), "=f"(d[57]), "=f"(d[58]), "=f"(d[59]), "=f"(d[60]), "=f"(d[61]), "=f"(d[62]), "=f"(d[63]), "=f"(d[64]), "=f"(d[65]), "=f"(d[66]), "=f"(d[67]), "=f"(d[68]), "=f"(d[69]), "=f"(d[70]), "=f"(d[71]), "=f"(d[72]), "=f"(d[73]), "=f"(d[74]), "=f"(d[75]), "=f"(d[76]), "=f"(d[77]), "=f"(d[78]), "=f"(d[79]), "=f"(d[80]), "=f"(d[81]), "=f"(d[82]), "=f"(d[83]), "=f"(d[84]), "=f"(d[85]), "=f"(d[86]), "=f"(d[87]), "=f"(d[88]), "=f"(d[89]), "=f"(d[90]), "=f"(d[91]), "=f"(d[92]), "=f"(d[93]), "=f"(d[94]), "=f"(d[95]), "=f"(d[96]), "=f"(d[97]), "=f"(d[98]), "=f"(d[99]), "=f"(d[100]), "=f"(d[101]), "=f"(d[102]), "=f"(d[103]), "=f"(d[104]), "=f"(d[105]), "=f"(d[106]), "=f"(d[107]), "=f"(d[108]), "=f"(d[109]), "=f"(d[110]), "=f"(d[111]), "=f"(d[112]), "=f"(d[113]), "=f"(d[114]), "=f"(d[115]), "=f"(d[116]), "=f"(d[117]), "=f"(d[118]), "=f"(d[119]), "=f"(d[120]), "=f"(d[121]), "=f"(d[122]), "=f"(d[123]), "=f"(d[124]), "=f"(d[125]), "=f"(d[126]), "=f"(d[127])
    : "l"(da), "l"(db));
  } else {
  asm volatile("{\n.reg .pred p;\nsetp.ne.b32 p, 1, 0;\nwgmma.mma_async.sync.aligned.m64n256k16.f32.bf16.bf16 {%0, %1, %2, %3, %4, %5, %6, %7, %8, %9, %10, %11, %12, %13, %14, %15, %16, %17, %18, %19, %20, %21, %22, %23, %24, %25, %26, %27, %28, %29, %30, %31, %32, %33, %34, %35, %36, %37, %38, %39, %40, %41, %42, %43, %44, %45, %46, %47, %48, %49, %50, %51, %52, %53, %54, %55, %56, %57, %58, %59, %60, %61, %62, %63, %64, %65, %66, %67, %68, %69, %70, %71, %72, %73, %74, %75, %76, %77, %78, %79, %80, %81, %82, %83, %84, %85, %86, %87, %88, %89, %90, %91, %92, %93, %94, %95, %96, %97, %98, %99, %100, %101, %102, %103, %104, %105, %106, %107, %108, %109, %110, %111, %112, %113, %114, %115, %116, %117, %118, %119, %120, %121, %122, %123, %124, %125, %126, %127}, %128, %129, p, 1, 1, 0, 1;\n}\n"
    : "+f"(d[0]), "+f"(d[1]), "+f"(d[2]), "+f"(d[3]), "+f"(d[4]), "+f"(d[5]), "+f"(d[6]), "+f"(d[7]), "+f"(d[8]), "+f"(d[9]), "+f"(d[10]), "+f"(d[11]), "+f"(d[12]), "+f"(d[13]), "+f"(d[14]), "+f"(d[15]), "+f"(d[16]), "+f"(d[17]), "+f"(d[18]), "+f"(d[19]), "+f"(d[20]), "+f"(d[21]), "+f"(d[22]), "+f"(d[23]), "+f"(d[24]), "+f"(d[25]), "+f"(d[26]), "+f"(d[27]), "+f"(d[28]), "+f"(d[29]), "+f"(d[30]), "+f"(d[31]), "+f"(d[32]), "+f"(d[33]), "+f"(d[34]), "+f"(d[35]), "+f"(d[36]), "+f"(d[37]), "+f"(d[38]), "+f"(d[39]), "+f"(d[40]), "+f"(d[41]), "+f"(d[42]), "+f"(d[43]), "+f"(d[44]), "+f"(d[45]), "+f"(d[46]), "+f"(d[47]), "+f"(d[48]), "+f"(d[49]), "+f"(d[50]), "+f"(d[51]), "+f"(d[52]), "+f"(d[53]), "+f"(d[54]), "+f"(d[55]), "+f"(d[56]), "+f"(d[57]), "+f"(d[58]), "+f"(d[59]), "+f"(d[60]), "+f"(d[61]), "+f"(d[62]), "+f"(d[63]), "+f"(d[64]), "+f"(d[65]), "+f"(d[66]), "+f"(d[67]), "+f"(d[68]), "+f"(d[69]), "+f"(d[70]), "+f"(d[71]), "+f"(d[72]), "+f"(d[73]), "+f"(d[74]), "+f"(d[75]), "+f"(d[76]), "+f"(d[77]), "+f"(d[78]), "+f"(d[79]), "+f"(d[80]), "+f"(d[81]), "+f"(d[82]), "+f"(d[83]), "+f"(d[84]), "+f"(d[85]), "+f"(d[86]), "+f"(d[87]), "+f"(d[88]), "+f"(d[89]), "+f"(d[90]), "+f"(d[91]), "+f"(d[92]), "+f"(d[93]), "+f"(d[94]), "+f"(d[95]), "+f"(d[96]), "+f"(d[97]), "+f"(d[98]), "+f"(d[99]), "+f"(d[100]), "+f"(d[101]), "+f"(d[102]), "+f"(d[103]), "+f"(d[104]), "+f"(d[105]), "+f"(d[106]), "+f"(d[107]), "+f"(d[108]), "+f"(d[109]), "+f"(d[110]), "+f"(d[111]), "+f"(d[112]), "+f"(d[113]), "+f"(d[114]), "+f"(d[115]), "+f"(d[116]), "+f"(d[117]), "+f"(d[118]), "+f"(d[119]), "+f"(d[120]), "+f"(d[121]), "+f"(d[122]), "+f"(d[123]), "+f"(d[124]), "+f"(d[125]), "+f"(d[126]), "+f"(d[127])
    : "l"(da), "l"(db));
  }
}
template<bool INIT> __device__ __forceinline__ void wgmma_n128_ss(float* d, uint64_t da, uint64_t db) {
  if constexpr (INIT) {
  asm volatile("{\n.reg .pred p;\nsetp.ne.b32 p, 0, 0;\nwgmma.mma_async.sync.aligned.m64n128k16.f32.bf16.bf16 {%0, %1, %2, %3, %4, %5, %6, %7, %8, %9, %10, %11, %12, %13, %14, %15, %16, %17, %18, %19, %20, %21, %22, %23, %24, %25, %26, %27, %28, %29, %30, %31, %32, %33, %34, %35, %36, %37, %38, %39, %40, %41, %42, %43, %44, %45, %46, %47, %48, %49, %50, %51, %52, %53, %54, %55, %56, %57, %58, %59, %60, %61, %62, %63}, %64, %65, p, 1, 1, 0, 1;\n}\n"
    : "=f"(d[0]), "=f"(d[1]), "=f"(d[2]), "=f"(d[3]), "=f"(d[4]), "=f"(d[5]), "=f"(d[6]), "=f"(d[7]), "=f"(d[8]), "=f"(d[9]), "=f"(d[10]), "=f"(d[11]), "=f"(d[12]), "=f"(d[13]), "=f"(d[14]), "=f"(d[15]), "=f"(d[16]), "=f"(d[17]), "=f"(d[18]), "=f"(d[19]), "=f"(d[20]), "=f"(d[21]), "=f"(d[22]), "=f"(d[23]), "=f"(d[24]), "=f"(d[25]), "=f"(d[26]), "=f"(d[27]), "=f"(d[28]), "=f"(d[29]), "=f"(d[30]), "=f"(d[31]), "=f"(d[32]), "=f"(d[33]), "=f"(d[34]), "=f"(d[35]), "=f"(d[36]), "=f"(d[37]), "=f"(d[38]), "=f"(d[39]), "=f"(d[40]), "=f"(d[41]), "=f"(d[42]), "=f"(d[43]), "=f"(d[44]), "=f"(d[45]), "=f"(d[46]), "=f"(d[47]), "=f"(d[48]), "=f"(d[49]), "=f"(d[50]), "=f"(d[51]), "=f"(d[52]), "=f"(d[53]), "=f"(d[54]), "=f"(d[55]), "=f"(d[56]), "=f"(d[57]), "=f"(d[58]), "=f"(d[59]), "=f"(d[60]), "=f"(d[61]), "=f"(d[62]), "=f"(d[63])
    : "l"(da), "l"(db));
  } else {
  asm volatile("{\n.reg .pred p;\nsetp.ne.b32 p, 1, 0;\nwgmma.mma_async.sync.aligned.m64n128k16.f32.bf16.bf16 {%0, %1, %2, %3, %4, %5, %6, %7, %8, %9, %10, %11, %12, %13, %14, %15, %16, %17, %18, %19, %20, %21, %22, %23, %24, %25, %26, %27, %28, %29, %30, %31, %32, %33, %34, %35, %36, %37, %38, %39, %40, %41, %42, %43, %44, %45, %46, %47, %48, %49, %50, %51, %52, %53, %54, %55, %56, %57, %58, %59, %60, %61, %62, %63}, %64, %65, p, 1, 1, 0, 1;\n}\n"
    : "+f"(d[0]), "+f"(d[1]), "+f"(d[2]), "+f"(d[3]), "+f"(d[4]), "+f"(d[5]), "+f"(d[6]), "+f"(d[7]), "+f"(d[8]), "+f"(d[9]), "+f"(d[10]), "+f"(d[11]), "+f"(d[12]), "+f"(d[13]), "+f"(d[14]), "+f"(d[15]), "+f"(d[16]), "+f"(d[17]), "+f"(d[18]), "+f"(d[19]), "+f"(d[20]), "+f"(d[21]), "+f"(d[22]), "+f"(d[23]), "+f"(d[24]), "+f"(d[25]), "+f"(d[26]), "+f"(d[27]), "+f"(d[28]), "+f"(d[29]), "+f"(d[30]), "+f"(d[31]), "+f"(d[32]), "+f"(d[33]), "+f"(d[34]), "+f"(d[35]), "+f"(d[36]), "+f"(d[37]), "+f"(d[38]), "+f"(d[39]), "+f"(d[40]), "+f"(d[41]), "+f"(d[42]), "+f"(d[43]), "+f"(d[44]), "+f"(d[45]), "+f"(d[46]), "+f"(d[47]), "+f"(d[48]), "+f"(d[49]), "+f"(d[50]), "+f"(d[51]), "+f"(d[52]), "+f"(d[53]), "+f"(d[54]), "+f"(d[55]), "+f"(d[56]), "+f"(d[57]), "+f"(d[58]), "+f"(d[59]), "+f"(d[60]), "+f"(d[61]), "+f"(d[62]), "+f"(d[63])
    : "l"(da), "l"(db));
  }
}
template<bool INIT> __device__ __forceinline__ void wgmma_n256_rs(float* d, const uint32_t* a, uint64_t db) {
  if constexpr (INIT) {
  asm volatile("{\n.reg .pred p;\nsetp.ne.b32 p, 0, 0;\nwgmma.mma_async.sync.aligned.m64n256k16.f32.bf16.bf16 {%0, %1, %2, %3, %4, %5, %6, %7, %8, %9, %10, %11, %12, %13, %14, %15, %16, %17, %18, %19, %20, %21, %22, %23, %24, %25, %26, %27, %28, %29, %30, %31, %32, %33, %34, %35, %36, %37, %38, %39, %40, %41, %42, %43, %44, %45, %46, %47, %48, %49, %50, %51, %52, %53, %54, %55, %56, %57, %58, %59, %60, %61, %62, %63, %64, %65, %66, %67, %68, %69, %70, %71, %72, %73, %74, %75, %76, %77, %78, %79, %80, %81, %82, %83, %84, %85, %86, %87, %88, %89, %90, %91, %92, %93, %94, %95, %96, %97, %98, %99, %100, %101, %102, %103, %104, %105, %106, %107, %108, %109, %110, %111, %112, %113, %114, %115, %116, %117, %118, %119, %120, %121, %122, %123, %124, %125, %126, %127}, {%128, %129, %130, %131}, %132, p, 1, 1, 1;\n}\n"
    : "=f"(d[0]), "=f"(d[1]), "=f"(d[2]), "=f"(d[3]), "=f"(d[4]), "=f"(d[5]), "=f"(d[6]), "=f"(d[7]), "=f"(d[8]), "=f"(d[9]), "=f"(d[10]), "=f"(d[11]), "=f"(d[12]), "=f"(d[13]), "=f"(d[14]), "=f"(d[15]), "=f"(d[16]), "=f"(d[17]), "=f"(d[18]), "=f"(d[19]), "=f"(d[20]), "=f"(d[21]), "=f"(d[22]), "=f"(d[23]), "=f"(d[24]), "=f"(d[25]), "=f"(d[26]), "=f"(d[27]), "=f"(d[28]), "=f"(d[29]), "=f"(d[30]), "=f"(d[31]), "=f"(d[32]), "=f"(d[33]), "=f"(d[34]), "=f"(d[35]), "=f"(d[36]), "=f"(d[37]), "=f"(d[38]), "=f"(d[39]), "=f"(d[40]), "=f"(d[41]), "=f"(d[42]), "=f"(d[43]), "=f"(d[44]), "=f"(d[45]), "=f"(d[46]), "=f"(d[47]), "=f"(d[48]), "=f"(d[49]), "=f"(d[50]), "=f"(d[51]), "=f"(d[52]), "=f"(d[53]), "=f"(d[54]), "=f"(d[55]), "=f"(d[56]), "=f"(d[57]), "=f"(d[58]), "=f"(d[59]), "=f"(d[60]), "=f"(d[61]), "=f"(d[62]), "=f"(d[63]), "=f"(d[64]), "=f"(d[65]), "=f"(d[66]), "=f"(d[67]), "=f"(d[68]), "=f"(d[69]), "=f"(d[70]), "=f"(d[71]), "=f"(d[72]), "=f"(d[73]), "=f"(d[74]), "=f"(d[75]), "=f"(d[76]), "=f"(d[77]), "=f"(d[78]), "=f"(d[79]), "=f"(d[80]), "=f"(d[81]), "=f"(d[82]), "=f"(d[83]), "=f"(d[84]), "=f"(d[85]), "=f"(d[86]), "=f"(d[87]), "=f"(d[88]), "=f"(d[89]), "=f"(d[90]), "=f"(d[91]), "=f"(d[92]), "=f"(d[93]), "=f"(d[94]), "=f"(d[95]), "=f"(d[96]), "=f"(d[97]), "=f"(d[98]), "=f"(d[99]), "=f"(d[100]), "=f"(d[101]), "=f"(d[102]), "=f"(d[103]), "=f"(d[104]), "=f"(d[105]), "=f"(d[106]), "=f"(d[107]), "=f"(d[108]), "=f"(d[109]), "=f"(d[110]), "=f"(d[111]), "=f"(d[112]), "=f"(d[113]), "=f"(d[114]), "=f"(d[115]), "=f"(d[116]), "=f"(d[117]), "=f"(d[118]), "=f"(d[119]), "=f"(d[120]), "=f"(d[121]), "=f"(d[122]), "=f"(d[123]), "=f"(d[124]), "=f"(d[125]), "=f"(d[126]), "=f"(d[127])
    : "r"(a[0]), "r"(a[1]), "r"(a[2]), "r"(a[3]), "l"(db));
  } else {
  asm volatile("{\n.reg .pred p;\nsetp.ne.b32 p, 1, 0;\nwgmma.mma_async.sync.aligned.m64n256k16.f32.bf16.bf16 {%0, %1, %2, %3, %4, %5, %6, %7, %8, %9, %10, %11, %12, %13, %14, %15, %16, %17, %18, %19, %20, %21, %22, %23, %24, %25, %26, %27, %28, %29, %30, %31, %32, %33, %34, %35, %36, %37, %38, %39, %40, %41, %42, %43, %44, %45, %46, %47, %48, %49, %50, %51, %52, %53, %54, %55, %56, %57, %58, %59, %60, %61, %62, %63, %64, %65, %66, %67, %68, %69, %70, %71, %72, %73, %74, %75, %76, %77, %78, %79, %80, %81, %82, %83, %84, %85, %86, %87, %88, %89, %90, %91, %92, %93, %94, %95, %96, %97, %98, %99, %100, %101, %102, %103, %104, %105, %106, %107, %108, %109, %110, %111, %112, %113, %114, %115, %116, %117, %118, %119, %120, %121, %122, %123, %124, %125, %126, %127}, {%128, %129, %130, %131}, %132, p, 1, 1, 1;\n}\n"
    : "+f"(d[0]), "+f"(d[1]), "+f"(d[2]), "+f"(d[3]), "+f"(d[4]), "+f"(d[5]), "+f"(d[6]), "+f"(d[7]), "+f"(d[8]), "+f"(d[9]), "+f"(d[10]), "+f"(d[11]), "+f"(d[12]), "+f"(d[13]), "+f"(d[14]), "+f"(d[15]), "+f"(d[16]), "+f"(d[17]), "+f"(d[18]), "+f"(d[19]), "+f"(d[20]), "+f"(d[21]), "+f"(d[22]), "+f"(d[23]), "+f"(d[24]), "+f"(d[25]), "+f"(d[26]), "+f"(d[27]), "+f"(d[28]), "+f"(d[29]), "+f"(d[30]), "+f"(d[31]), "+f"(d[32]), "+f"(d[33]), "+f"(d[34]), "+f"(d[35]), "+f"(d[36]), "+f"(d[37]), "+f"(d[38]), "+f"(d[39]), "+f"(d[40]), "+f"(d[41]), "+f"(d[42]), "+f"(d[43]), "+f"(d[44]), "+f"(d[45]), "+f"(d[46]), "+f"(d[47]), "+f"(d[48]), "+f"(d[49]), "+f"(d[50]), "+f"(d[51]), "+f"(d[52]), "+f"(d[53]), "+f"(d[54]), "+f"(d[55]), "+f"(d[56]), "+f"(d[57]), "+f"(d[58]), "+f"(d[59]), "+f"(d[60]), "+f"(d[61]), "+f"(d[62]), "+f"(d[63]), "+f"(d[64]), "+f"(d[65]), "+f"(d[66]), "+f"(d[67]), "+f"(d[68]), "+f"(d[69]), "+f"(d[70]), "+f"(d[71]), "+f"(d[72]), "+f"(d[73]), "+f"(d[74]), "+f"(d[75]), "+f"(d[76]), "+f"(d[77]), "+f"(d[78]), "+f"(d[79]), "+f"(d[80]), "+f"(d[81]), "+f"(d[82]), "+f"(d[83]), "+f"(d[84]), "+f"(d[85]), "+f"(d[86]), "+f"(d[87]), "+f"(d[88]), "+f"(d[89]), "+f"(d[90]), "+f"(d[91]), "+f"(d[92]), "+f"(d[93]), "+f"(d[94]), "+f"(d[95]), "+f"(d[96]), "+f"(d[97]), "+f"(d[98]), "+f"(d[99]), "+f"(d[100]), "+f"(d[101]), "+f"(d[102]), "+f"(d[103]), "+f"(d[104]), "+f"(d[105]), "+f"(d[106]), "+f"(d[107]), "+f"(d[108]), "+f"(d[109]), "+f"(d[110]), "+f"(d[111]), "+f"(d[112]), "+f"(d[113]), "+f"(d[114]), "+f"(d[115]), "+f"(d[116]), "+f"(d[117]), "+f"(d[118]), "+f"(d[119]), "+f"(d[120]), "+f"(d[121]), "+f"(d[122]), "+f"(d[123]), "+f"(d[124]), "+f"(d[125]), "+f"(d[126]), "+f"(d[127])
    : "r"(a[0]), "r"(a[1]), "r"(a[2]), "r"(a[3]), "l"(db));
  }
}
template<bool INIT> __device__ __forceinline__ void wgmma_n128_rs(float* d, const uint32_t* a, uint64_t db) {
  if constexpr (INIT) {
  asm volatile("{\n.reg .pred p;\nsetp.ne.b32 p, 0, 0;\nwgmma.mma_async.sync.aligned.m64n128k16.f32.bf16.bf16 {%0, %1, %2, %3, %4, %5, %6, %7, %8, %9, %10, %11, %12, %13, %14, %15, %16, %17, %18, %19, %20, %21, %22, %23, %24, %25, %26, %27, %28, %29, %30, %31, %32, %33, %34, %35, %36, %37, %38, %39, %40, %41, %42, %43, %44, %45, %46, %47, %48, %49, %50, %51, %52, %53, %54, %55, %56, %57, %58, %59, %60, %61, %62, %63}, {%64, %65, %66, %67}, %68, p, 1, 1, 1;\n}\n"
    : "=f"(d[0]), "=f"(d[1]), "=f"(d[2]), "=f"(d[3]), "=f"(d[4]), "=f"(d[5]), "=f"(d[6]), "=f"(d[7]), "=f"(d[8]), "=f"(d[9]), "=f"(d[10]), "=f"(d[11]), "=f"(d[12]), "=f"(d[13]), "=f"(d[14]), "=f"(d[15]), "=f"(d[16]), "=f"(d[17]), "=f"(d[18]), "=f"(d[19]), "=f"(d[20]), "=f"(d[21]), "=f"(d[22]), "=f"(d[23]), "=f"(d[24]), "=f"(d[25]), "=f"(d[26]), "=f"(d[27]), "=f"(d[28]), "=f"(d[29]), "=f"(d[30]), "=f"(d[31]), "=f"(d[32]), "=f"(d[33]), "=f"(d[34]), "=f"(d[35]), "=f"(d[36]), "=f"(d[37]), "=f"(d[38]), "=f"(d[39]), "=f"(d[40]), "=f"(d[41]), "=f"(d[42]), "=f"(d[43]), "=f"(d[44]), "=f"(d[45]), "=f"(d[46]), "=f"(d[47]), "=f"(d[48]), "=f"(d[49]), "=f"(d[50]), "=f"(d[51]), "=f"(d[52]), "=f"(d[53]), "=f"(d[54]), "=f"(d[55]), "=f"(d[56]), "=f"(d[57]), "=f"(d[58]), "=f"(d[59]), "=f"(d[60]), "=f"(d[61]), "=f"(d[62]), "=f"(d[63])
    : "r"(a[0]), "r"(a[1]), "r"(a[2]), "r"(a[3]), "l"(db));
  } else {
  asm volatile("{\n.reg .pred p;\nsetp.ne.b32 p, 1, 0;\nwgmma.mma_async.sync.aligned.m64n128k16.f32.bf16.bf16 {%0, %1, %2, %3, %4, %5, %6, %7, %8, %9, %10, %11, %12, %13, %14, %15, %16, %17, %18, %19, %20, %21, %22, %23, %24, %25, %26, %27, %28, %29, %30, %31, %32, %33, %34, %35, %36, %37, %38, %39, %40, %41, %42, %43, %44, %45, %46, %47, %48, %49, %50, %51, %52, %53, %54, %55, %56, %57, %58, %59, %60, %61, %62, %63}, {%64, %65, %66, %67}, %68, p, 1, 1, 1;\n}\n"
    : "+f"(d[0]), "+f"(d[1]), "+f"(d[2]), "+f"(d[3]), "+f"(d[4]), "+f"(d[5]), "+f"(d[6]), "+f"(d[7]), "+f"(d[8]), "+f"(d[9]), "+f"(d[10]), "+f"(d[11]), "+f"(d[12]), "+f"(d[13]), "+f"(d[14]), "+f"(d[15]), "+f"(d[16]), "+f"(d[17]), "+f"(d[18]), "+f"(d[19]), "+f"(d[20]), "+f"(d[21]), "+f"(d[22]), "+f"(d[23]), "+f"(d[24]), "+f"(d[25]), "+f"(d[26]), "+f"(d[27]), "+f"(d[28]), "+f"(d[29]), "+f"(d[30]), "+f"(d[31]), "+f"(d[32]), "+f"(d[33]), "+f"(d[34]), "+f"(d[35]), "+f"(d[36]), "+f"(d[37]), "+f"(d[38]), "+f"(d[39]), "+f"(d[40]), "+f"(d[41]), "+f"(d[42]), "+f"(d[43]), "+f"(d[44]), "+f"(d[45]), "+f"(d[46]), "+f"(d[47]), "+f"(d[48]), "+f"(d[49]), "+f"(d[50]), "+f"(d[51]), "+f"(d[52]), "+f"(d[53]), "+f"(d[54]), "+f"(d[55]), "+f"(d[56]), "+f"(d[57]), "+f"(d[58]), "+f"(d[59]), "+f"(d[60]), "+f"(d[61]), "+f"(d[62]), "+f"(d[63])
    : "r"(a[0]), "r"(a[1]), "r"(a[2]), "r"(a[3]), "l"(db));
  }
}
template<bool INIT> __device__ __forceinline__ void wgmma_n64_tt(float* d, uint64_t da, uint64_t db) {
  if constexpr (INIT) {
  asm volatile("{\n.reg .pred p;\nsetp.ne.b32 p, 0, 0;\nwgmma.mma_async.sync.aligned.m64n64k16.f32.bf16.bf16 {%0, %1, %2, %3, %4, %5, %6, %7, %8, %9, %10, %11, %12, %13, %14, %15, %16, %17, %18, %19, %20, %21, %22, %23, %24, %25, %26, %27, %28, %29, %30, %31}, %32, %33, p, 1, 1, 1, 1;\n}\n"
    : "=f"(d[0]), "=f"(d[1]), "=f"(d[2]), "=f"(d[3]), "=f"(d[4]), "=f"(d[5]), "=f"(d[6]), "=f"(d[7]), "=f"(d[8]), "=f"(d[9]), "=f"(d[10]), "=f"(d[11]), "=f"(d[12]), "=f"(d[13]), "=f"(d[14]), "=f"(d[15]), "=f"(d[16]), "=f"(d[17]), "=f"(d[18]), "=f"(d[19]), "=f"(d[20]), "=f"(d[21]), "=f"(d[22]), "=f"(d[23]), "=f"(d[24]), "=f"(d[25]), "=f"(d[26]), "=f"(d[27]), "=f"(d[28]), "=f"(d[29]), "=f"(d[30]), "=f"(d[31])
    : "l"(da), "l"(db));
  } else {
  asm volatile("{\n.reg .pred p;\nsetp.ne.b32 p, 1, 0;\nwgmma.mma_async.sync.aligned.m64n64k16.f32.bf16.bf16 {%0, %1, %2, %3, %4, %5, %6, %7, %8, %9, %10, %11, %12, %13, %14, %15, %16, %17, %18, %19, %20, %21, %22, %23, %24, %25, %26, %27, %28, %29, %30, %31}, %32, %33, p, 1, 1, 1, 1;\n}\n"
    : "+f"(d[0]), "+f"(d[1]), "+f"(d[2]), "+f"(d[3]), "+f"(d[4]), "+f"(d[5]), "+f"(d[6]), "+f"(d[7]), "+f"(d[8]), "+f"(d[9]), "+f"(d[10]), "+f"(d[11]), "+f"(d[12]), "+f"(d[13]), "+f"(d[14]), "+f"(d[15]), "+f"(d[16]), "+f"(d[17]), "+f"(d[18]), "+f"(d[19]), "+f"(d[20]), "+f"(d[21]), "+f"(d[22]), "+f"(d[23]), "+f"(d[24]), "+f"(d[25]), "+f"(d[26]), "+f"(d[27]), "+f"(d[28]), "+f"(d[29]), "+f"(d[30]), "+f"(d[31])
    : "l"(da), "l"(db));
  }
}
template<bool INIT> __device__ __forceinline__ void wgmma_n8_tn(float* d, uint64_t da, uint64_t db) {
  if constexpr (INIT) {
  asm volatile("{\n.reg .pred p;\nsetp.ne.b32 p, 0, 0;\nwgmma.mma_async.sync.aligned.m64n8k16.f32.bf16.bf16 {%0, %1, %2, %3}, %4, %5, p, 1, 1, 1, 0;\n}\n"
    : "=f"(d[0]), "=f"(d[1]), "=f"(d[2]), "=f"(d[3])
    : "l"(da), "l"(db));
  } else {
  asm volatile("{\n.reg .pred p;\nsetp.ne.b32 p, 1, 0;\nwgmma.mma_async.sync.aligned.m64n8k16.f32.bf16.bf16 {%0, %1, %2, %3}, %4, %5, p, 1, 1, 1, 0;\n}\n"
    : "+f"(d[0]), "+f"(d[1]), "+f"(d[2]), "+f"(d[3])
    : "l"(da), "l"(db));
  }
}
template<bool INIT> __device__ __forceinline__ void wgmma_n40_rs(float* d, const uint32_t* a, uint64_t db) {
  if constexpr (INIT) {
  asm volatile("{\n.reg .pred p;\nsetp.ne.b32 p, 0, 0;\nwgmma.mma_async.sync.aligned.m64n40k16.f32.bf16.bf16 {%0, %1, %2, %3, %4, %5, %6, %7, %8, %9, %10, %11, %12, %13, %14, %15, %16, %17, %18, %19}, {%20, %21, %22, %23}, %24, p, 1, 1, 1;\n}\n"
    : "=f"(d[0]), "=f"(d[1]), "=f"(d[2]), "=f"(d[3]), "=f"(d[4]), "=f"(d[5]), "=f"(d[6]), "=f"(d[7]), "=f"(d[8]), "=f"(d[9]), "=f"(d[10]), "=f"(d[11]), "=f"(d[12]), "=f"(d[13]), "=f"(d[14]), "=f"(d[15]), "=f"(d[16]), "=f"(d[17]), "=f"(d[18]), "=f"(d[19])
    : "r"(a[0]), "r"(a[1]), "r"(a[2]), "r"(a[3]), "l"(db));
  } else {
  asm volatile("{\n.reg .pred p;\nsetp.ne.b32 p, 1, 0;\nwgmma.mma_async.sync.aligned.m64n40k16.f32.bf16.bf16 {%0, %1, %2, %3, %4, %5, %6, %7, %8, %9, %10, %11, %12, %13, %14, %15, %16, %17, %18, %19}, {%20, %21, %22, %23}, %24, p, 1, 1, 1;\n}\n"
    : "+f"(d[0]), "+f"(d[1]), "+f"(d[2]), "+f"(d[3]), "+f"(d[4]), "+f"(d[5]), "+f"(d[6]), "+f"(d[7]), "+f"(d[8]), "+f"(d[9]), "+f"(d[10]), "+f"(d[11]), "+f"(d[12]), "+f"(d[13]), "+f"(d[14]), "+f"(d[15]), "+f"(d[16]), "+f"(d[17]), "+f"(d[18]), "+f"(d[19])
    : "r"(a[0]), "r"(a[1]), "r"(a[2]), "r"(a[3]), "l"(db));
  }
}

__device__ __forceinline__ void quad_transpose(uint32_t& r0, uint32_t& r1, uint32_t& r2, uint32_t& r3, int c) {
  bool o1 = c & 1, o2 = c & 2;
  uint32_t t0 = o1 ? r0 : r1, t1 = o1 ? r2 : r3;
  t0 = __shfl_xor_sync(~0u, t0, 1); t1 = __shfl_xor_sync(~0u, t1, 1);
  if (o1) { r0 = t0; r2 = t1; } else { r1 = t0; r3 = t1; }
  t0 = o2 ? r0 : r2; t1 = o2 ? r1 : r3;
  t0 = __shfl_xor_sync(~0u, t0, 2); t1 = __shfl_xor_sync(~0u, t1, 2);
  if (o2) { r0 = t0; r1 = t1; } else { r2 = t0; r3 = t1; }
}

struct Ring {
  uint32_t slot, phase;
  __device__ __forceinline__ void next() { if (++slot == NSLOT) { slot = 0; phase ^= 1; } }
};
struct Step { uint32_t a, pa, b, pb0, pb1; };
template<int NB> __device__ __forceinline__ Step take_step(Ring& r) {
  Step s;
  if (NB == 2 && r.slot == NSLOT - 2) {
    s.b = r.slot; s.pb0 = r.phase; s.pb1 = r.phase; r.next(); r.next();
    s.a = r.slot; s.pa = r.phase; r.next();
  } else {
    s.a = r.slot; s.pa = r.phase; r.next();
    s.b = r.slot; s.pb0 = r.phase; s.pb1 = r.phase; r.next();
    if (NB == 2) r.next();
  }
  return s;
}

__device__ __forceinline__ int kb16(int i, int j) { return (2 * j + i) & 15; }
__device__ __forceinline__ void kb56(int i, int j, int& kb, int& fi) {
  int t, jj, e;
  if (i < 48) { t = i >> 4; jj = (i & 15) >> 1; e = i & 1; } else { t = 3; jj = i - 48; e = 0; }
  int jp = (j + jj) & 7;
  kb = 7 * jp + 2 * t + e; fi = t * 8 + jp;
}

template<int NB, bool FIRST>
__device__ __forceinline__ void kstep(float* acc, Ring& ring, uint32_t& rel0, uint32_t& rel1, uint32_t sbase, uint32_t bars, int cw, int tid) {
  Step st = take_step<NB>(ring);
  mbar_wait(bars + 8 * st.b, st.pb0);
  if (NB == 2) mbar_wait(bars + 8 * (st.b + 1), st.pb1);
  mbar_wait(bars + 8 * st.a, st.pa);
  uint64_t da = make_desc(sbase + st.a * SLOT + cw * 8192, 16, 1024);
  uint64_t db = make_desc(sbase + st.b * SLOT, 8192, 1024);
  wgmma_fence();
  if (NB == 2) wgmma_n256_ss<FIRST>(acc, da, db); else wgmma_n128_ss<FIRST>(acc, da, db);
#pragma unroll
  for (int kk = 1; kk < 4; kk++) {
    if (NB == 2) wgmma_n256_ss<false>(acc, da + kk * 2, db + kk * 128);
    else wgmma_n128_ss<false>(acc, da + kk * 2, db + kk * 128);
  }
  wgmma_commit();
  if (!FIRST) {
    wgmma_wait<1>();
    if (tid < 2 * (NB + 1)) { uint32_t sl = tid < 2 ? rel0 : rel1 + (tid >> 1) - 1; mbar_arrive_cluster(bars + 8 * (NSLOT + sl), tid & 1); }
  }
  rel0 = st.a; rel1 = st.b;
}

template<int NB>
__device__ __forceinline__ void mainloop(float* acc, int nsteps, Ring& ring, uint32_t sbase, uint32_t bars, int cw, int tid) {
  uint32_t rel0, rel1;
  kstep<NB, true>(acc, ring, rel0, rel1, sbase, bars, cw, tid);
#pragma unroll 1
  for (int i = 1; i < nsteps; i++) kstep<NB, false>(acc, ring, rel0, rel1, sbase, bars, cw, tid);
  wgmma_wait<0>();
  if (tid < 2 * (NB + 1)) { uint32_t sl = tid < 2 ? rel0 : rel1 + (tid >> 1) - 1; mbar_arrive_cluster(bars + 8 * (NSLOT + sl), tid & 1); }
}

__device__ __forceinline__ void load_stats(const float2 (*st)[8], int row, int c, float& mean0, float& rstd0, float& mean1, float& rstd1) {
  float4 a = __ldcg((const float4*)&st[row][2 * c]);
  float4 b = __ldcg((const float4*)&st[row + 8][2 * c]);
  float ma = a.x + a.z, mb = b.x + b.z;
  ma += __shfl_xor_sync(~0u, ma, 1); mb += __shfl_xor_sync(~0u, mb, 1);
  ma += __shfl_xor_sync(~0u, ma, 2); mb += __shfl_xor_sync(~0u, mb, 2);
  ma *= 0.125f; mb *= 0.125f;
  float va = a.y + a.w + 128.f * ((a.x - ma) * (a.x - ma) + (a.z - ma) * (a.z - ma));
  float vb = b.y + b.w + 128.f * ((b.x - mb) * (b.x - mb) + (b.z - mb) * (b.z - mb));
  va += __shfl_xor_sync(~0u, va, 1); vb += __shfl_xor_sync(~0u, vb, 1);
  va += __shfl_xor_sync(~0u, va, 2); vb += __shfl_xor_sync(~0u, vb, 2);
  mean0 = ma; mean1 = mb;
  rstd0 = rsqrtf(va * (1.f / 1024.f) + 1e-5f); rstd1 = rsqrtf(vb * (1.f / 1024.f) + 1e-5f);
}

__device__ __forceinline__ void store_img(uint8_t* img, const uint32_t* P, int ngroups, int rloc, int g, int c) {
#pragma unroll
  for (int gi = 0; gi < 4; gi++) {
    if (gi < ngroups) {
      uint8_t* p = img + (gi >> 1) * SLOT + rloc * 128 + ((((gi & 1) * 4 + c) ^ g) << 4);
      *(uint4*)p = make_uint4(P[8 * gi], P[8 * gi + 2], P[8 * gi + 4], P[8 * gi + 6]);
      *(uint4*)(p + 1024) = make_uint4(P[8 * gi + 1], P[8 * gi + 3], P[8 * gi + 5], P[8 * gi + 7]);
    }
  }
}

template<int NB>
__device__ __forceinline__ void glu_epilogue(const float* acc, uint32_t cs_addr, float mean0, float rstd0, float mean1, float rstd1, uint8_t* img, int rloc, int g, int c) {
  uint32_t P[16 * NB];
#pragma unroll
  for (int hf = 0; hf < NB; hf++) {
#pragma unroll
    for (int b = 0; b < 8; b++) {
      int bg = hf * 16 + b, bu = bg + 8;
      float2 cg = lds_f2(cs_addr + bg * 32), cu = lds_f2(cs_addr + bu * 32);
      float h[4];
#pragma unroll
      for (int q = 0; q < 4; q++) {
        float mean = q < 2 ? mean0 : mean1, rstd = q < 2 ? rstd0 : rstd1;
        float gg = rstd * (acc[4 * bg + q] - mean * ((q & 1) ? cg.y : cg.x));
        float uu = rstd * (acc[4 * bu + q] - mean * ((q & 1) ? cu.y : cu.x));
        h[q] = gg * uu * rcpf(1.f + ex2f(gg * -1.4426950408889634f));
      }
      P[hf * 16 + 2 * b] = pack_bf16(h[0], h[1]); P[hf * 16 + 2 * b + 1] = pack_bf16(h[2], h[3]);
    }
  }
  store_img(img, P, 2 * NB, rloc, g, c);
}

#define TR(i)

__global__ void __launch_bounds__(384, 1) fused_kernel(const __grid_constant__ Params prm) {
  extern __shared__ __align__(1024) uint8_t smem_raw[];
  const uint32_t sbase = smem_u32(smem_raw);
  const uint32_t bars = sbase + OFF_BAR;
  const uint32_t bar_kvdone = bars + 8 * 24, bar_kvready = bars + 8 * 25, bar_sig = bars + 8 * 26;
  const int warp = threadIdx.x >> 5, lane = threadIdx.x & 31;
  const int rank = blockIdx.x & 1;
  const int m = ((blockIdx.x >> 1) & 7) * 2 + rank;
  const int j = blockIdx.x >> 4;

  if (threadIdx.x == 0) {
    if (sbase & 1023) __trap();
    for (int s = 0; s < NSLOT; s++) { mbar_init(bars + 8 * s, 1); mbar_init(bars + 8 * (NSLOT + s), 4); }
    mbar_init(bar_kvdone, 8); mbar_init(bar_kvready, 2); mbar_init(bar_sig, 4); mbar_init(bar_sig + 8, 4);
    asm volatile("fence.mbarrier_init.release.cluster;" ::: "memory");
  }
  if (threadIdx.x < 64) sts_u32(sbase + OFF_ONES + threadIdx.x * 4, 0x3F803F80u);
  {
    int t = threadIdx.x;
    int col = t < 256 ? ((t >> 6) & 1 ? 2048 : 1024) + 128 * j + (t >> 7) * 64 + (t & 63) : 128 * j + (t - 256);
    sts_u32(sbase + OFF_CSQ + t * 4, __float_as_uint(__ldcg(&g_cs[col])));
  }
  fence_async_smem();
  const uint32_t epoch = __ldcg(&g_epoch) + 1;
  __syncthreads();
  cluster_sync();

  if (warp < 4) {
    asm volatile("setmaxnreg.dec.sync.aligned.u32 40;");
    if (warp == 0) {
      if (lane == 0) {
        Ring ring{0, 0};
        for (int layer = 0; layer < 2; layer++) {
          for (int tile = 0; tile < 8; tile++) {
            const CUtensorMap* map; int col; int nsteps = 16; bool two = false;
            if (tile == 0) { map = layer ? &prm.wqkv_p : &prm.wqkv_n; col = 1024 + 1024 * rank + 128 * j; two = true; }
            else if (tile == 1) { map = layer ? &prm.wqkv_p : &prm.wqkv_n; col = 128 * j + 64 * rank; }
            else if (tile == 2) { map = &prm.wo_p; col = 128 * j + 64 * rank; }
            else if (tile < 7) { map = rank ? &prm.wu_p : &prm.wg_p; col = 448 * j + 128 * (tile - 3); two = tile < 6; }
            else { map = &prm.wd_p; col = 128 * j + 64 * rank; nsteps = 56; }
            for (int i = 0; i < nsteps; i++) {
              int kb, fi;
              if (tile == 7) kb56(i, j, kb, fi); else kb = kb16(i, j);
              Step st = two ? take_step<2>(ring) : take_step<1>(ring);
              mbar_wait(bars + 8 * (NSLOT + st.b), st.pb0 ^ 1);
              mbar_expect_tx(bars + 8 * st.b, SLOT);
              tma_5d_mc(sbase + st.b * SLOT + rank * 8192, map, bars + 8 * st.b, col, kb * 2);
              if (two) {
                mbar_wait(bars + 8 * (NSLOT + st.b + 1), st.pb1 ^ 1);
                mbar_expect_tx(bars + 8 * (st.b + 1), SLOT);
                tma_5d_mc(sbase + (st.b + 1) * SLOT + rank * 8192, map, bars + 8 * (st.b + 1), col + 64, kb * 2);
              }
            }
          }
        }
      }
    } else if (warp == 1) {
      Ring ring{0, 0};
      for (int layer = 0; layer < 2; layer++) {
        uint32_t ready = 0;
        for (int tile = 0; tile < 8; tile++) {
          const uint8_t* img; const uint32_t* fl; int nsteps = 16; bool two = tile == 0 || (tile >= 3 && tile < 6);
          if (tile < 2) { img = g_x2 + m * 16 * SLOT; fl = g_flag[0][3][m]; if (tile == 0) ready = layer ? 0 : ~0u; }
          else if (tile == 2) { img = g_o + m * 16 * SLOT; fl = g_flag[layer][0][m]; ready = 0; }
          else if (tile < 7) { img = g_x1 + m * 16 * SLOT; fl = g_flag[layer][1][m]; if (tile == 3) ready = 0; }
          else { img = g_h + m * 56 * SLOT; fl = g_flag[layer][2][m]; ready = 0; nsteps = 56; }
          for (int i = 0; i < nsteps; i++) {
            int kb, fi;
            if (tile == 7) kb56(i, j, kb, fi); else { kb = kb16(i, j); fi = kb >> 1; }
            Step st = two ? take_step<2>(ring) : take_step<1>(ring);
            if (!((ready >> fi) & 1)) {
              uint32_t n = 0;
              do {
                uint32_t v = ld_acquire(fl + lane);
                ready = __ballot_sync(~0u, v == epoch);
                if (++n > (1u << 20)) __trap();
              } while (!((ready >> fi) & 1));
              fence_async_global();
            }
            if (lane == 0) {
              mbar_wait(bars + 8 * (NSLOT + st.a), st.pa ^ 1);
              mbar_expect_tx(bars + 8 * st.a, SLOT);
              if (layer == 0 && tile < 2) tma_2d(sbase + st.a * SLOT, &prm.x, bars + 8 * st.a, kb * 64, m * 128);
              else bulk_load(sbase + st.a * SLOT, img + kb * SLOT, SLOT, bars + 8 * st.a);
            }
            __syncwarp();
          }
        }
      }
    } else {
      const int w = warp - 2;
      {
        float* z = &g_kv[(epoch & 1) ^ 1][0][0][0] + (size_t)blockIdx.x * 528;
        for (int i = w * 32 + lane; i < 132; i += 64) *(float4*)(z + i * 4) = make_float4(0.f, 0.f, 0.f, 0.f);
      }
      uint32_t sigph = 0;
      for (int layer = 0; layer < 2; layer++) {
        mbar_wait(bar_kvdone, layer);
        if (w == 0) { if (lane == 0) { fence_gpu(); red_add_u32(&g_kvcnt[layer][j][0], 1); } }
        else {
          for (int t = lane; t < 896; t += 32) {
            int col = 3072 + ((t >> 6) & 1) * F_ + 448 * j + (t >> 7) * 64 + (t & 63);
            sts_u32(sbase + OFF_CSGU + t * 4, __float_as_uint(__ldcg(&g_cs[col])));
          }
        }
        {
          uint32_t n = 0;
          while (ld_acquire(&g_kvcnt[layer][j][0]) != epoch * 16) { if (++n > (1u << 20)) __trap(); }
        }
        const float* kvp = &g_kv[epoch & 1][layer][4 * j + 2 * w][0];
#pragma unroll 1
        for (int hh = 0; hh < 2; hh++) {
          float4 v[8];
#pragma unroll
          for (int q = 0; q < 8; q++) v[q] = __ldcg((const float4*)(kvp + hh * 1056 + (q * 32 + lane) * 4));
          float zz = __ldcg(kvp + hh * 1056 + 1024 + lane);
          uint32_t hb = sbase + OFF_STG + (2 * w + hh) * 4096;
#pragma unroll
          for (int q = 0; q < 8; q++) {
            int idx = (q * 32 + lane) * 4;
            int d = idx >> 5, c = (idx >> 3) & 3, jb = (idx >> 1) & 3;
            uint32_t rb = hb + d * 128 + c * 4;
            sts_u32(rb + ((jb ^ (d & 7)) << 4), pack_bf16(v[q].x, v[q].y));
            sts_u32(rb + (((jb + 1) ^ (d & 7)) << 4), pack_bf16(v[q].z, v[q].w));
          }
          uint32_t zp = pack_bf16(zz, zz);
          sts_v4(hb + lane * 128 + ((4 ^ (lane & 7)) << 4), make_uint4(zp, zp, zp, zp));
        }
        fence_async_smem();
        __syncwarp();
        if (lane == 0) mbar_arrive(bar_kvready);
        if (w == 0) {
          for (int ev = 0; ev < 7; ev++) {
            if (layer == 1 && ev == 6) break;
            mbar_wait(bar_sig, sigph); mbar_wait(bar_sig + 8, sigph); sigph ^= 1;
            if (lane == 0) {
              uint32_t* f = ev == 0 ? &g_flag[layer][0][m][j] : ev == 1 ? &g_flag[layer][1][m][j] : ev < 6 ? &g_flag[layer][2][m][(ev - 2) * 8 + j] : &g_flag[0][3][m][j];
              fence_gpu();
              st_relaxed(f, epoch);
            }
            __syncwarp();
          }
        }
      }
    }
  } else {
    asm volatile("setmaxnreg.inc.sync.aligned.u32 232;");
    const int cw = (threadIdx.x >> 7) - 1, tid = threadIdx.x & 127, w4 = warp & 3, g = lane >> 2, c = lane & 3;
    const int rloc = cw * 64 + w4 * 16 + g;
    const int row = m * 128 + rloc;
    Ring ring{0, 0};
    TR(0);
#pragma unroll 1
    for (int layer = 0; layer < 2; layer++) {
      float mean0, rstd0, mean1, rstd1;
      {
        float acc[128];
        mainloop<2>(acc, 16, ring, sbase, bars, cw, tid);
        TR(1 + layer * 16);
        load_stats(g_stats[layer * 2], row, c, mean0, rstd0, mean1, rstd1);
        const uint32_t stg = sbase + OFF_STG + cw * 16384;
        const int srow = w4 * 16 + ((lane >> 3) & 1) * 8 + (lane & 7);
        const uint32_t sta = stg + srow * 128;
        float* kvdst = &g_kv[epoch & 1][layer][4 * j + (w4 >> 1)][0];
#pragma unroll
        for (int p = 0; p < 2; p++) {
#pragma unroll
          for (int half = 0; half < 2; half++) {
#pragma unroll
            for (int jb = 0; jb < 8; jb += 2) {
              uint32_t r[4];
#pragma unroll
              for (int q = 0; q < 2; q++) {
                int b = p * 16 + half * 8 + jb + q;
                float2 cs = lds_f2(sbase + OFF_CSQ + (b * 8 + 2 * c) * 4);
                float v0 = rstd0 * (acc[4 * b] - mean0 * cs.x), v1 = rstd0 * (acc[4 * b + 1] - mean0 * cs.y);
                float v2 = rstd1 * (acc[4 * b + 2] - mean1 * cs.x), v3 = rstd1 * (acc[4 * b + 3] - mean1 * cs.y);
                if (half == 0) { v0 = phif(v0); v1 = phif(v1); v2 = phif(v2); v3 = phif(v3); }
                r[2 * q] = pack_bf16(v0, v1); r[2 * q + 1] = pack_bf16(v2, v3);
              }
              stmatrix_x4(sta + half * 8192 + (((jb + (lane >> 4)) ^ (lane & 7)) << 4), r[0], r[1], r[2], r[3]);
            }
          }
          fence_async_smem();
          wg_bar(1 + cw);
          float kv[32], z[4];
          uint64_t da = make_desc(stg, 8192, 1024), db = make_desc(stg + 8192, 8192, 1024);
          uint64_t dones = (uint64_t)(((sbase + OFF_ONES) & 0x3FFFF) >> 4) | (8ull << 16) | (8ull << 32);
          wgmma_fence();
          wgmma_n64_tt<true>(kv, da, db);
#pragma unroll
          for (int kk = 1; kk < 4; kk++) wgmma_n64_tt<false>(kv, da + kk * 128, db + kk * 128);
          wgmma_n8_tn<true>(z, da, dones);
#pragma unroll
          for (int kk = 1; kk < 4; kk++) wgmma_n8_tn<false>(z, da + kk * 128, dones);
          wgmma_commit();
          wgmma_wait<0>();
          {
            bool hi = w4 >= 2;
            float* dst = kvdst + p * 2 * 1056;
            int d0 = (w4 & 1) * 16 + g;
            float s[16];
#pragma unroll
            for (int i = 0; i < 16; i++) s[i] = hi ? kv[16 + i] : kv[i];
            red_add_v4(dst + d0 * 32 + c * 8, s[0], s[1], s[4], s[5]);
            red_add_v4(dst + d0 * 32 + c * 8 + 4, s[8], s[9], s[12], s[13]);
            red_add_v4(dst + (d0 + 8) * 32 + c * 8, s[2], s[3], s[6], s[7]);
            red_add_v4(dst + (d0 + 8) * 32 + c * 8 + 4, s[10], s[11], s[14], s[15]);
            if (c == 0) { red_add_f32(dst + 1024 + d0, z[0]); red_add_f32(dst + 1024 + d0 + 8, z[2]); }
          }
          wg_bar(1 + cw);
        }
        __syncwarp();
        if (lane == 0) mbar_arrive(bar_kvdone);
      }
      TR(2 + layer * 16);
      {
        float acc[64];
        mainloop<1>(acc, 16, ring, sbase, bars, cw, tid);
        TR(3 + layer * 16);
        uint32_t P[32];
#pragma unroll
        for (int b = 0; b < 16; b++) {
          float2 cs = lds_f2(sbase + OFF_CSQ + (256 + b * 8 + 2 * c) * 4);
          float v0 = rstd0 * (acc[4 * b] - mean0 * cs.x), v1 = rstd0 * (acc[4 * b + 1] - mean0 * cs.y);
          float v2 = rstd1 * (acc[4 * b + 2] - mean1 * cs.x), v3 = rstd1 * (acc[4 * b + 3] - mean1 * cs.y);
          P[2 * b] = pack_bf16(phif(v0), phif(v1)); P[2 * b + 1] = pack_bf16(phif(v2), phif(v3));
        }
        mbar_wait(bar_kvready, layer);
        float num[4][20];
        wgmma_fence();
#pragma unroll
        for (int hh = 0; hh < 4; hh++) {
          uint64_t db = make_desc(sbase + OFF_STG + hh * 4096, 8192, 1024);
          wgmma_n40_rs<true>(num[hh], P + 8 * hh, db);
          wgmma_n40_rs<false>(num[hh], P + 8 * hh + 4, db + 128);
        }
        wgmma_commit();
        wgmma_wait<0>();
#pragma unroll
        for (int hh = 0; hh < 4; hh++) {
          float r0 = rcpf(num[hh][16] + 1e-6f), r1 = rcpf(num[hh][18] + 1e-6f);
#pragma unroll
          for (int b = 0; b < 4; b++) {
            P[8 * hh + 2 * b] = pack_bf16(num[hh][4 * b] * r0, num[hh][4 * b + 1] * r0);
            P[8 * hh + 2 * b + 1] = pack_bf16(num[hh][4 * b + 2] * r1, num[hh][4 * b + 3] * r1);
          }
        }
        store_img(g_o + (m * 16 + 2 * j) * SLOT, P, 4, rloc, g, c);
        __syncwarp();
        if (lane == 0) mbar_arrive(bar_sig + 8 * cw);
      }
      TR(4 + layer * 16);
#pragma unroll 1
      for (int half = 0; half < 2; half++) {
        if (half == 1) {
#pragma unroll 1
          for (int t = 0; t < 3; t++) {
            float acc[128];
            mainloop<2>(acc, 16, ring, sbase, bars, cw, tid);
            TR(7 + 2 * t + layer * 16);
            if (t == 0) load_stats(g_stats[layer * 2 + 1], row, c, mean0, rstd0, mean1, rstd1);
            glu_epilogue<2>(acc, sbase + OFF_CSGU + (t * 256 + 2 * c) * 4, mean0, rstd0, mean1, rstd1, g_h + (m * 56 + 7 * j + 2 * t) * SLOT, rloc, g, c);
            __syncwarp();
            if (lane == 0) mbar_arrive(bar_sig + 8 * cw);
            TR(8 + 2 * t + layer * 16);
          }
          {
            float acc[64];
            mainloop<1>(acc, 16, ring, sbase, bars, cw, tid);
            TR(13 + layer * 16);
            glu_epilogue<1>(acc, sbase + OFF_CSGU + (3 * 256 + 2 * c) * 4, mean0, rstd0, mean1, rstd1, g_h + (m * 56 + 7 * j + 6) * SLOT, rloc, g, c);
            __syncwarp();
            if (lane == 0) mbar_arrive(bar_sig + 8 * cw);
            TR(14 + layer * 16);
          }
        }
        float acc[64];
        mainloop<1>(acc, half ? 56 : 16, ring, sbase, bars, cw, tid);
        TR((half ? 15 : 5) + layer * 16);
        uint32_t P[32];
        if (layer == 0 && half == 0) {
#pragma unroll
          for (int gi = 0; gi < 4; gi++) {
            const __nv_bfloat16* p = prm.xin + (size_t)row * D_ + 128 * j + 32 * gi + 8 * c;
            uint4 a = __ldg((const uint4*)p), b = __ldg((const uint4*)(p + 8 * D_));
            quad_transpose(a.x, a.y, a.z, a.w, c); quad_transpose(b.x, b.y, b.z, b.w, c);
            P[8 * gi] = a.x; P[8 * gi + 2] = a.y; P[8 * gi + 4] = a.z; P[8 * gi + 6] = a.w;
            P[8 * gi + 1] = b.x; P[8 * gi + 3] = b.y; P[8 * gi + 5] = b.z; P[8 * gi + 7] = b.w;
          }
        } else {
          const uint8_t* img = (half ? g_x1 : g_x2) + (m * 16 + 2 * j) * SLOT;
#pragma unroll
          for (int gi = 0; gi < 4; gi++) {
            const uint8_t* p = img + (gi >> 1) * SLOT + rloc * 128 + ((((gi & 1) * 4 + c) ^ g) << 4);
            uint4 a = __ldcg((const uint4*)p), b = __ldcg((const uint4*)(p + 1024));
            P[8 * gi] = a.x; P[8 * gi + 2] = a.y; P[8 * gi + 4] = a.z; P[8 * gi + 6] = a.w;
            P[8 * gi + 1] = b.x; P[8 * gi + 3] = b.y; P[8 * gi + 5] = b.z; P[8 * gi + 7] = b.w;
          }
        }
        float s0 = 0.f, s1 = 0.f;
#pragma unroll
        for (int b = 0; b < 16; b++) {
          P[2 * b] = pack_bf16(bf_lo(P[2 * b]) + acc[4 * b], bf_hi(P[2 * b]) + acc[4 * b + 1]);
          P[2 * b + 1] = pack_bf16(bf_lo(P[2 * b + 1]) + acc[4 * b + 2], bf_hi(P[2 * b + 1]) + acc[4 * b + 3]);
          s0 += bf_lo(P[2 * b]) + bf_hi(P[2 * b]); s1 += bf_lo(P[2 * b + 1]) + bf_hi(P[2 * b + 1]);
        }
        if (layer == 1 && half == 1) {
#pragma unroll
          for (int gi = 0; gi < 4; gi++) {
            quad_transpose(P[8 * gi], P[8 * gi + 2], P[8 * gi + 4], P[8 * gi + 6], c);
            quad_transpose(P[8 * gi + 1], P[8 * gi + 3], P[8 * gi + 5], P[8 * gi + 7], c);
            __nv_bfloat16* p = prm.out + (size_t)row * D_ + 128 * j + 32 * gi + 8 * c;
            *(uint4*)p = make_uint4(P[8 * gi], P[8 * gi + 2], P[8 * gi + 4], P[8 * gi + 6]);
            *(uint4*)(p + 8 * D_) = make_uint4(P[8 * gi + 1], P[8 * gi + 3], P[8 * gi + 5], P[8 * gi + 7]);
          }
        } else {
          store_img((half ? g_x2 : g_x1) + (m * 16 + 2 * j) * SLOT, P, 4, rloc, g, c);
          s0 += __shfl_xor_sync(~0u, s0, 1); s1 += __shfl_xor_sync(~0u, s1, 1);
          s0 += __shfl_xor_sync(~0u, s0, 2); s1 += __shfl_xor_sync(~0u, s1, 2);
          s0 *= (1.f / 128.f); s1 *= (1.f / 128.f);
          float q0 = 0.f, q1 = 0.f;
#pragma unroll
          for (int b = 0; b < 16; b++) {
            float a0 = bf_lo(P[2 * b]) - s0, a1 = bf_hi(P[2 * b]) - s0, b0 = bf_lo(P[2 * b + 1]) - s1, b1 = bf_hi(P[2 * b + 1]) - s1;
            q0 += a0 * a0 + a1 * a1; q1 += b0 * b0 + b1 * b1;
          }
          q0 += __shfl_xor_sync(~0u, q0, 1); q1 += __shfl_xor_sync(~0u, q1, 1);
          q0 += __shfl_xor_sync(~0u, q0, 2); q1 += __shfl_xor_sync(~0u, q1, 2);
          if (c == 0) {
            float2 (*st)[8] = g_stats[layer * 2 + 1 + half];
            st[row][j] = make_float2(s0, q0); st[row + 8][j] = make_float2(s1, q1);
          }
          __syncwarp();
          if (lane == 0) mbar_arrive(bar_sig + 8 * cw);
        }
        TR((half ? 16 : 6) + layer * 16);
      }
    }
    if (blockIdx.x == 0 && threadIdx.x == 128) g_epoch = epoch;
  }
  __syncwarp();
  cluster_sync();
}

__global__ void __launch_bounds__(256) pre_kernel(const __nv_bfloat16* x, const __nv_bfloat16* wqkv, const __nv_bfloat16* wg, const __nv_bfloat16* wu) {
  __shared__ float red[8][64];
  const int warp = threadIdx.x >> 5, lane = threadIdx.x & 31;
  if (blockIdx.x < 160) {
    int col0 = blockIdx.x * 64;
    const __nv_bfloat16* w; int ld, cc;
    if (col0 < 3072) { w = wqkv; ld = 3072; cc = col0; } else if (col0 < 3072 + F_) { w = wg; ld = F_; cc = col0 - 3072; } else { w = wu; ld = F_; cc = col0 - 3072 - F_; }
    float s[8] = {0, 0, 0, 0, 0, 0, 0, 0};
    const int r0 = threadIdx.x >> 3, ch = threadIdx.x & 7;
#pragma unroll 8
    for (int r = r0; r < 1024; r += 32) {
      uint4 v = __ldg((const uint4*)(w + (size_t)r * ld + cc + ch * 8));
      s[0] += bf_lo(v.x); s[1] += bf_hi(v.x); s[2] += bf_lo(v.y); s[3] += bf_hi(v.y);
      s[4] += bf_lo(v.z); s[5] += bf_hi(v.z); s[6] += bf_lo(v.w); s[7] += bf_hi(v.w);
    }
#pragma unroll
    for (int i = 0; i < 8; i++) { s[i] += __shfl_xor_sync(~0u, s[i], 8); s[i] += __shfl_xor_sync(~0u, s[i], 16); }
    if (lane < 8) for (int i = 0; i < 8; i++) red[warp][lane * 8 + i] = s[i];
    __syncthreads();
    if (threadIdx.x < 64) { float t = 0; for (int i = 0; i < 8; i++) t += red[i][threadIdx.x]; g_cs[col0 + threadIdx.x] = t; }
  } else {
    int row = (blockIdx.x - 160) * 8 + warp;
    const uint4* p = (const uint4*)(x + (size_t)row * D_ + lane * 32);
    float v[32];
#pragma unroll
    for (int i = 0; i < 4; i++) {
      uint4 u = __ldg(p + i);
      v[8 * i] = bf_lo(u.x); v[8 * i + 1] = bf_hi(u.x); v[8 * i + 2] = bf_lo(u.y); v[8 * i + 3] = bf_hi(u.y);
      v[8 * i + 4] = bf_lo(u.z); v[8 * i + 5] = bf_hi(u.z); v[8 * i + 6] = bf_lo(u.w); v[8 * i + 7] = bf_hi(u.w);
    }
    float s = 0;
#pragma unroll
    for (int i = 0; i < 32; i++) s += v[i];
    s += __shfl_xor_sync(~0u, s, 1); s += __shfl_xor_sync(~0u, s, 2);
    s *= (1.f / 128.f);
    float q = 0;
#pragma unroll
    for (int i = 0; i < 32; i++) q += (v[i] - s) * (v[i] - s);
    q += __shfl_xor_sync(~0u, q, 1); q += __shfl_xor_sync(~0u, q, 2);
    if ((lane & 3) == 0) g_stats[0][row][lane >> 2] = make_float2(s, q);
  }
}

typedef CUresult (*EncodeTiledFn)(CUtensorMap*, CUtensorMapDataType, cuuint32_t, void*, const cuuint64_t*, const cuuint64_t*, const cuuint32_t*, const cuuint32_t*,
                                  CUtensorMapInterleave, CUtensorMapSwizzle, CUtensorMapL2promotion, CUtensorMapFloatOOBfill);

void make_wmap(EncodeTiledFn enc, CUtensorMap* m, const void* ptr, uint64_t rows, uint64_t cols, bool perm) {
  uint64_t rs = cols * 2;
  cuuint64_t gd[5] = {cols, 2, 4, 4, rows / 32};
  cuuint64_t gs[4] = {rs, (perm ? 8 : 2) * rs, (perm ? 2 : 8) * rs, 32 * rs};
  cuuint32_t bd[5] = {64, 2, 4, 4, 2}, es[5] = {1, 1, 1, 1, 1};
  enc(m, CU_TENSOR_MAP_DATA_TYPE_BFLOAT16, 5, (void*)ptr, gd, gs, bd, es, CU_TENSOR_MAP_INTERLEAVE_NONE, CU_TENSOR_MAP_SWIZZLE_128B,
      CU_TENSOR_MAP_L2_PROMOTION_L2_256B, CU_TENSOR_MAP_FLOAT_OOB_FILL_NONE);
}

}

extern "C" void kernel_launch(void* const* d_in, const int* in_sizes, int n_in, void* d_out, int out_size) {
  const __nv_bfloat16* x = (const __nv_bfloat16*)d_in[0];
  const __nv_bfloat16* wqkv = (const __nv_bfloat16*)d_in[1];
  const __nv_bfloat16* wo = (const __nv_bfloat16*)d_in[2];
  const __nv_bfloat16* wg = (const __nv_bfloat16*)d_in[4];
  const __nv_bfloat16* wu = (const __nv_bfloat16*)d_in[5];
  const __nv_bfloat16* wd = (const __nv_bfloat16*)d_in[6];

  void* fn = nullptr; cudaDriverEntryPointQueryResult qr;
  cudaGetDriverEntryPoint("cuTensorMapEncodeTiled", &fn, cudaEnableDefault, &qr);
  EncodeTiledFn enc = (EncodeTiledFn)fn;
  Params prm;
  {
    cuuint64_t gd[2] = {D_, S_}, gs[1] = {D_ * 2}; cuuint32_t bd[2] = {64, 128}, es[2] = {1, 1};
    enc(&prm.x, CU_TENSOR_MAP_DATA_TYPE_BFLOAT16, 2, (void*)x, gd, gs, bd, es, CU_TENSOR_MAP_INTERLEAVE_NONE, CU_TENSOR_MAP_SWIZZLE_128B,
        CU_TENSOR_MAP_L2_PROMOTION_L2_256B, CU_TENSOR_MAP_FLOAT_OOB_FILL_NONE);
  }
  make_wmap(enc, &prm.wqkv_n, wqkv, D_, 3 * D_, false);
  make_wmap(enc, &prm.wqkv_p, wqkv, D_, 3 * D_, true);
  make_wmap(enc, &prm.wo_p, wo, D_, D_, true);
  make_wmap(enc, &prm.wg_p, wg, D_, F_, true);
  make_wmap(enc, &prm.wu_p, wu, D_, F_, true);
  make_wmap(enc, &prm.wd_p, wd, F_, D_, true);
  prm.xin = x; prm.out = (__nv_bfloat16*)d_out;

  cudaFuncSetAttribute(fused_kernel, cudaFuncAttributeMaxDynamicSharedMemorySize, SMEM_BYTES);
  pre_kernel<<<160 + 256, 256, 0, cudaStreamPerThread>>>(x, wqkv, wg, wu);
  cudaLaunchConfig_t cfg = {};
  cfg.gridDim = dim3(128); cfg.blockDim = dim3(384); cfg.dynamicSmemBytes = SMEM_BYTES; cfg.stream = cudaStreamPerThread;
  cudaLaunchAttribute at[1];
  at[0].id = cudaLaunchAttributeClusterDimension; at[0].val.clusterDim.x = 2; at[0].val.clusterDim.y = 1; at[0].val.clusterDim.z = 1;
  cfg.attrs = at; cfg.numAttrs = 1;
  cudaLaunchKernelEx(&cfg, fused_kernel, prm);
}
```

```cpp
#include <cuda_runtime.h>
#include <cuda_bf16.h>
#include <cuda.h>
#include <stdint.h>

namespace {

constexpr int S_ = 2048, D_ = 1024, F_ = 3584;
constexpr int NSLOT = 12;
constexpr uint32_t SLOT = 16384;
constexpr uint32_t OFF_STG = NSLOT * SLOT;
constexpr uint32_t OFF_CSQ = OFF_STG + 32768;
constexpr uint32_t OFF_ONES = OFF_CSQ + 1536;
constexpr uint32_t OFF_BAR = OFF_ONES + 256;
constexpr uint32_t SMEM_BYTES = OFF_BAR + 512;
constexpr uint32_t OFF_CSGU = OFF_STG + 16384;

__device__ __align__(1024) uint8_t g_o[16 * 16 * SLOT];
__device__ __align__(1024) uint8_t g_x1[16 * 16 * SLOT];
__device__ __align__(1024) uint8_t g_x2[16 * 16 * SLOT];
__device__ __align__(1024) uint8_t g_h[16 * 56 * SLOT];
__device__ __align__(128) float2 g_stats[4][S_][8];
__device__ __align__(128) float g_cs[3072 + 2 * F_];
__device__ __align__(128) float g_kv[2][2][32][1056];
__device__ __align__(128) uint32_t g_flag[2][4][16][32];
__device__ __align__(128) uint32_t g_kvcnt[2][8][32];
__device__ __align__(128) uint32_t g_cscnt[2][32];
__device__ uint32_t g_epoch;

struct Params {
  CUtensorMap x, wqkv_n, wqkv_p, wo_n, wo_p, wg_n, wg_p, wu_n, wu_p, wd_p, hq, hg, hu;
  const __nv_bfloat16* xin;
  __nv_bfloat16* out;
};

__device__ __forceinline__ uint32_t smem_u32(const void* p) { return (uint32_t)__cvta_generic_to_shared(p); }
__device__ __forceinline__ void mbar_init(uint32_t bar, uint32_t count) { asm volatile("mbarrier.init.shared::cta.b64 [%0], %1;" :: "r"(bar), "r"(count) : "memory"); }
__device__ __forceinline__ void mbar_expect_tx(uint32_t bar, uint32_t bytes) { asm volatile("mbarrier.arrive.expect_tx.shared::cta.b64 _, [%0], %1;" :: "r"(bar), "r"(bytes) : "memory"); }
__device__ __forceinline__ void mbar_arrive(uint32_t bar) { asm volatile("mbarrier.arrive.shared::cta.b64 _, [%0];" :: "r"(bar) : "memory"); }
__device__ __forceinline__ void mbar_arrive_cluster(uint32_t bar, uint32_t cta) {
  asm volatile("{\n.reg .b32 ra;\nmapa.shared::cluster.u32 ra, %0, %1;\nmbarrier.arrive.shared::cluster.b64 _, [ra];\n}\n" :: "r"(bar), "r"(cta) : "memory");
}
__device__ __forceinline__ void mbar_arrive_if(uint32_t bar, bool pred) {
  asm volatile("{\n.reg .pred p;\nsetp.ne.b32 p, %1, 0;\n@p mbarrier.arrive.shared::cta.b64 _, [%0];\n}\n" :: "r"(bar), "r"((uint32_t)pred) : "memory");
}
__device__ __forceinline__ void mbar_arrive_remote_if(uint32_t cluster_addr, bool pred) {
  asm volatile("{\n.reg .pred p;\nsetp.ne.b32 p, %1, 0;\n@p mbarrier.arrive.shared::cluster.b64 _, [%0];\n}\n" :: "r"(cluster_addr), "r"((uint32_t)pred) : "memory");
}
__device__ __forceinline__ uint32_t mapa(uint32_t addr, uint32_t cta) { uint32_t r; asm("mapa.shared::cluster.u32 %0, %1, %2;" : "=r"(r) : "r"(addr), "r"(cta)); return r; }
__device__ __forceinline__ void st_f2_if(float2* ptr, float a, float b, bool pred) {
  asm volatile("{\n.reg .pred p;\nsetp.ne.b32 p, %3, 0;\n@p st.global.v2.f32 [%0], {%1, %2};\n}\n" :: "l"(ptr), "f"(a), "f"(b), "r"((uint32_t)pred) : "memory");
}
__device__ __forceinline__ void red_add_f32_if(float* ptr, float v, bool pred) {
  asm volatile("{\n.reg .pred p;\nsetp.ne.b32 p, %2, 0;\n@p red.relaxed.gpu.global.add.f32 [%0], %1;\n}\n" :: "l"(ptr), "f"(v), "r"((uint32_t)pred) : "memory");
}
__device__ __forceinline__ void mbar_wait(uint32_t bar, uint32_t parity) {
  asm volatile("{\n.reg .pred p;\n.reg .b32 n;\nmov.b32 n, 0;\nWAIT_LOOP:\n"
               "mbarrier.try_wait.parity.shared::cta.b64 p, [%0], %1;\n@p bra WAIT_DONE;\n"
               "add.u32 n, n, 1;\nsetp.lt.u32 p, n, 1048576;\n@p bra WAIT_LOOP;\ntrap;\nWAIT_DONE:\n}\n" :: "r"(bar), "r"(parity) : "memory");
}
__device__ __forceinline__ uint32_t ld_acquire(const uint32_t* p) { uint32_t v; asm volatile("ld.acquire.gpu.global.u32 %0, [%1];" : "=r"(v) : "l"(p) : "memory"); return v; }
__device__ __forceinline__ void poll_eq(const uint32_t* p, uint32_t want) {
  uint32_t n = 0;
  while (ld_acquire(p) != want) { if (++n > (1u << 20)) __trap(); }
}
__device__ __forceinline__ void tma_2d(uint32_t dst, const CUtensorMap* m, uint32_t bar, int c0, int c1) {
  asm volatile("cp.async.bulk.tensor.2d.shared::cluster.global.mbarrier::complete_tx::bytes [%0], [%1, {%3, %4}], [%2];"
    :: "r"(dst), "l"((uint64_t)m), "r"(bar), "r"(c0), "r"(c1) : "memory");
}
__device__ __forceinline__ void tma_5d_mc(uint32_t dst, const CUtensorMap* m, uint32_t bar, int c0, int c4) {
  asm volatile("cp.async.bulk.tensor.5d.shared::cluster.global.mbarrier::complete_tx::bytes.multicast::cluster [%0], [%1, {%3, %5, %5, %5, %4}], [%2], %6;"
    :: "r"(dst), "l"((uint64_t)m), "r"(bar), "r"(c0), "r"(c4), "r"(0), "h"((uint16_t)3) : "memory");
}
__device__ __forceinline__ void tma_5d_prefetch(const CUtensorMap* m, int c0, int c4) {
  asm volatile("cp.async.bulk.prefetch.tensor.5d.L2.global.tile [%0, {%1, %3, %3, %3, %2}];" :: "l"((uint64_t)m), "r"(c0), "r"(c4), "r"(0) : "memory");
}
__device__ __forceinline__ void bulk_load(uint32_t dst, const void* src, uint32_t bytes, uint32_t bar) {
  asm volatile("cp.async.bulk.shared::cluster.global.mbarrier::complete_tx::bytes [%0], [%1], %2, [%3];"
    :: "r"(dst), "l"((uint64_t)src), "r"(bytes), "r"(bar) : "memory");
}
__device__ __forceinline__ void wgmma_fence() { asm volatile("wgmma.fence.sync.aligned;" ::: "memory"); }
__device__ __forceinline__ void wgmma_commit() { asm volatile("wgmma.commit_group.sync.aligned;" ::: "memory"); }
template<int N> __device__ __forceinline__ void wgmma_wait() { asm volatile("wgmma.wait_group.sync.aligned %0;" :: "n"(N) : "memory"); }
__device__ __forceinline__ void cluster_sync() { asm volatile("barrier.cluster.arrive.release.aligned;\nbarrier.cluster.wait.acquire.aligned;" ::: "memory"); }
__device__ __forceinline__ void fence_async_smem() { asm volatile("fence.proxy.async.shared::cta;" ::: "memory"); }
__device__ __forceinline__ void fence_async_global() { asm volatile("fence.proxy.async.global;" ::: "memory"); }
__device__ __forceinline__ void fence_gpu() { asm volatile("fence.acq_rel.gpu;" ::: "memory"); }
__device__ __forceinline__ void wg_bar(int id) { asm volatile("bar.sync %0, 128;" :: "r"(id) : "memory"); }
__device__ __forceinline__ void st_relaxed(uint32_t* p, uint32_t v) { asm volatile("st.relaxed.gpu.global.u32 [%0], %1;" :: "l"(p), "r"(v) : "memory"); }
__device__ __forceinline__ void red_add_u32(uint32_t* p, uint32_t v) { asm volatile("red.relaxed.gpu.global.add.u32 [%0], %1;" :: "l"(p), "r"(v) : "memory"); }
__device__ __forceinline__ void red_add_f32(float* p, float v) { asm volatile("red.relaxed.gpu.global.add.f32 [%0], %1;" :: "l"(p), "f"(v) : "memory"); }
__device__ __forceinline__ void red_add_v4(float* p, float a, float b, float c, float d) {
  asm volatile("red.relaxed.gpu.global.add.v4.f32 [%0], {%1, %2, %3, %4};" :: "l"(p), "f"(a), "f"(b), "f"(c), "f"(d) : "memory");
}
__device__ __forceinline__ void stmatrix_x4(uint32_t addr, uint32_t r0, uint32_t r1, uint32_t r2, uint32_t r3) {
  asm volatile("stmatrix.sync.aligned.m8n8.x4.shared.b16 [%0], {%1, %2, %3, %4};" :: "r"(addr), "r"(r0), "r"(r1), "r"(r2), "r"(r3) : "memory");
}
__device__ __forceinline__ float2 lds_f2(uint32_t addr) { float2 v; asm volatile("ld.shared.v2.f32 {%0, %1}, [%2];" : "=f"(v.x), "=f"(v.y) : "r"(addr)); return v; }
__device__ __forceinline__ void sts_u32(uint32_t addr, uint32_t v) { asm volatile("st.shared.u32 [%0], %1;" :: "r"(addr), "r"(v) : "memory"); }
__device__ __forceinline__ void sts_v4(uint32_t addr, uint4 v) { asm volatile("st.shared.v4.u32 [%0], {%1, %2, %3, %4};" :: "r"(addr), "r"(v.x), "r"(v.y), "r"(v.z), "r"(v.w) : "memory"); }
__device__ __forceinline__ uint32_t pack_bf16(float lo, float hi) { uint32_t r; asm("cvt.rn.bf16x2.f32 %0, %1, %2;" : "=r"(r) : "f"(hi), "f"(lo)); return r; }
__device__ __forceinline__ float bf_lo(uint32_t v) { return __uint_as_float(v << 16); }
__device__ __forceinline__ float bf_hi(uint32_t v) { return __uint_as_float(v & 0xffff0000u); }
__device__ __forceinline__ float ex2f(float x) { float r; asm("ex2.approx.ftz.f32 %0, %1;" : "=f"(r) : "f"(x)); return r; }
__device__ __forceinline__ float rcpf(float x) { float r; asm("rcp.approx.ftz.f32 %0, %1;" : "=f"(r) : "f"(x)); return r; }
__device__ __forceinline__ float phif(float t) { return (t > 0.f ? t + 1.f : ex2f(t * 1.4426950408889634f)) + 1e-6f; }
__device__ __forceinline__ uint32_t make_desc(uint32_t addr, uint32_t lbo) { return ((addr & 0x3FFFF) >> 4) | ((lbo >> 4) << 16); }
__device__ __forceinline__ bool mbar_test(uint32_t bar, uint32_t parity) {
  uint32_t ok;
  asm volatile("{\n.reg .pred p;\nmbarrier.test_wait.parity.shared::cta.b64 p, [%1], %2;\nselp.u32 %0, 1, 0, p;\n}\n" : "=r"(ok) : "r"(bar), "r"(parity) : "memory");
  return ok;
}
__device__ __forceinline__ bool elect_one() {
  uint32_t r;
  asm volatile("{\n.reg .pred p;\nelect.sync _|p, 0xffffffff;\nselp.u32 %0, 1, 0, p;\n}\n" : "=r"(r));
  return r;
}
__device__ __forceinline__ uint32_t hmul2(uint32_t a, uint32_t b) { uint32_t r; asm("mul.rn.bf16x2 %0, %1, %2;" : "=r"(r) : "r"(a), "r"(b)); return r; }
__device__ __forceinline__ unsigned long long gtime() { unsigned long long t; asm volatile("mov.u64 %0, %%globaltimer;" : "=l"(t)); return t; }

template<bool INIT> __device__ __forceinline__ void wgmma_n256_ss(float* d, uint32_t da, uint32_t db) {
  if constexpr (INIT) {
  asm volatile("{\n.reg .pred p;\n.reg .b64 da, db;\nsetp.ne.b32 p, 0, 0;\nmov.b64 da, {%128, 0x40000040};\nmov.b64 db, {%129, 0x40000040};\nwgmma.mma_async.sync.aligned.m64n256k16.f32.bf16.bf16 {%0, %1, %2, %3, %4, %5, %6, %7, %8, %9, %10, %11, %12, %13, %14, %15, %16, %17, %18, %19, %20, %21, %22, %23, %24, %25, %26, %27, %28, %29, %30, %31, %32, %33, %34, %35, %36, %37, %38, %39, %40, %41, %42, %43, %44, %45, %46, %47, %48, %49, %50, %51, %52, %53, %54, %55, %56, %57, %58, %59, %60, %61, %62, %63, %64, %65, %66, %67, %68, %69, %70, %71, %72, %73, %74, %75, %76, %77, %78, %79, %80, %81, %82, %83, %84, %85, %86, %87, %88, %89, %90, %91, %92, %93, %94, %95, %96, %97, %98, %99, %100, %101, %102, %103, %104, %105, %106, %107, %108, %109, %110, %111, %112, %113, %114, %115, %116, %117, %118, %119, %120, %121, %122, %123, %124, %125, %126, %127}, da, db, p, 1, 1, 0, 1;\n}\n"
    : "=f"(d[0]), "=f"(d[1]), "=f"(d[2]), "=f"(d[3]), "=f"(d[4]), "=f"(d[5]), "=f"(d[6]), "=f"(d[7]), "=f"(d[8]), "=f"(d[9]), "=f"(d[10]), "=f"(d[11]), "=f"(d[12]), "=f"(d[13]), "=f"(d[14]), "=f"(d[15]), "=f"(d[16]), "=f"(d[17]), "=f"(d[18]), "=f"(d[19]), "=f"(d[20]), "=f"(d[21]), "=f"(d[22]), "=f"(d[23]), "=f"(d[24]), "=f"(d[25]), "=f"(d[26]), "=f"(d[27]), "=f"(d[28]), "=f"(d[29]), "=f"(d[30]), "=f"(d[31]), "=f"(d[32]), "=f"(d[33]), "=f"(d[34]), "=f"(d[35]), "=f"(d[36]), "=f"(d[37]), "=f"(d[38]), "=f"(d[39]), "=f"(d[40]), "=f"(d[41]), "=f"(d[42]), "=f"(d[43]), "=f"(d[44]), "=f"(d[45]), "=f"(d[46]), "=f"(d[47]), "=f"(d[48]), "=f"(d[49]), "=f"(d[50]), "=f"(d[51]), "=f"(d[52]), "=f"(d[53]), "=f"(d[54]), "=f"(d[55]), "=f"(d[56]), "=f"(d[57]), "=f"(d[58]), "=f"(d[59]), "=f"(d[60]), "=f"(d[61]), "=f"(d[62]), "=f"(d[63]), "=f"(d[64]), "=f"(d[65]), "=f"(d[66]), "=f"(d[67]), "=f"(d[68]), "=f"(d[69]), "=f"(d[70]), "=f"(d[71]), "=f"(d[72]), "=f"(d[73]), "=f"(d[74]), "=f"(d[75]), "=f"(d[76]), "=f"(d[77]), "=f"(d[78]), "=f"(d[79]), "=f"(d[80]), "=f"(d[81]), "=f"(d[82]), "=f"(d[83]), "=f"(d[84]), "=f"(d[85]), "=f"(d[86]), "=f"(d[87]), "=f"(d[88]), "=f"(d[89]), "=f"(d[90]), "=f"(d[91]), "=f"(d[92]), "=f"(d[93]), "=f"(d[94]), "=f"(d[95]), "=f"(d[96]), "=f"(d[97]), "=f"(d[98]), "=f"(d[99]), "=f"(d[100]), "=f"(d[101]), "=f"(d[102]), "=f"(d[103]), "=f"(d[104]), "=f"(d[105]), "=f"(d[106]), "=f"(d[107]), "=f"(d[108]), "=f"(d[109]), "=f"(d[110]), "=f"(d[111]), "=f"(d[112]), "=f"(d[113]), "=f"(d[114]), "=f"(d[115]), "=f"(d[116]), "=f"(d[117]), "=f"(d[118]), "=f"(d[119]), "=f"(d[120]), "=f"(d[121]), "=f"(d[122]), "=f"(d[123]), "=f"(d[124]), "=f"(d[125]), "=f"(d[126]), "=f"(d[127])
    : "r"(da), "r"(db));
  } else {
  asm volatile("{\n.reg .pred p;\n.reg .b64 da, db;\nsetp.ne.b32 p, 1, 0;\nmov.b64 da, {%128, 0x40000040};\nmov.b64 db, {%129, 0x40000040};\nwgmma.mma_async.sync.aligned.m64n256k16.f32.bf16.bf16 {%0, %1, %2, %3, %4, %5, %6, %7, %8, %9, %10, %11, %12, %13, %14, %15, %16, %17, %18, %19, %20, %21, %22, %23, %24, %25, %26, %27, %28, %29, %30, %31, %32, %33, %34, %35, %36, %37, %38, %39, %40, %41, %42, %43, %44, %45, %46, %47, %48, %49, %50, %51, %52, %53, %54, %55, %56, %57, %58, %59, %60, %61, %62, %63, %64, %65, %66, %67, %68, %69, %70, %71, %72, %73, %74, %75, %76, %77, %78, %79, %80, %81, %82, %83, %84, %85, %86, %87, %88, %89, %90, %91, %92, %93, %94, %95, %96, %97, %98, %99, %100, %101, %102, %103, %104, %105, %106, %107, %108, %109, %110, %111, %112, %113, %114, %115, %116, %117, %118, %119, %120, %121, %122, %123, %124, %125, %126, %127}, da, db, p, 1, 1, 0, 1;\n}\n"
    : "+f"(d[0]), "+f"(d[1]), "+f"(d[2]), "+f"(d[3]), "+f"(d[4]), "+f"(d[5]), "+f"(d[6]), "+f"(d[7]), "+f"(d[8]), "+f"(d[9]), "+f"(d[10]), "+f"(d[11]), "+f"(d[12]), "+f"(d[13]), "+f"(d[14]), "+f"(d[15]), "+f"(d[16]), "+f"(d[17]), "+f"(d[18]), "+f"(d[19]), "+f"(d[20]), "+f"(d[21]), "+f"(d[22]), "+f"(d[23]), "+f"(d[24]), "+f"(d[25]), "+f"(d[26]), "+f"(d[27]), "+f"(d[28]), "+f"(d[29]), "+f"(d[30]), "+f"(d[31]), "+f"(d[32]), "+f"(d[33]), "+f"(d[34]), "+f"(d[35]), "+f"(d[36]), "+f"(d[37]), "+f"(d[38]), "+f"(d[39]), "+f"(d[40]), "+f"(d[41]), "+f"(d[42]), "+f"(d[43]), "+f"(d[44]), "+f"(d[45]), "+f"(d[46]), "+f"(d[47]), "+f"(d[48]), "+f"(d[49]), "+f"(d[50]), "+f"(d[51]), "+f"(d[52]), "+f"(d[53]), "+f"(d[54]), "+f"(d[55]), "+f"(d[56]), "+f"(d[57]), "+f"(d[58]), "+f"(d[59]), "+f"(d[60]), "+f"(d[61]), "+f"(d[62]), "+f"(d[63]), "+f"(d[64]), "+f"(d[65]), "+f"(d[66]), "+f"(d[67]), "+f"(d[68]), "+f"(d[69]), "+f"(d[70]), "+f"(d[71]), "+f"(d[72]), "+f"(d[73]), "+f"(d[74]), "+f"(d[75]), "+f"(d[76]), "+f"(d[77]), "+f"(d[78]), "+f"(d[79]), "+f"(d[80]), "+f"(d[81]), "+f"(d[82]), "+f"(d[83]), "+f"(d[84]), "+f"(d[85]), "+f"(d[86]), "+f"(d[87]), "+f"(d[88]), "+f"(d[89]), "+f"(d[90]), "+f"(d[91]), "+f"(d[92]), "+f"(d[93]), "+f"(d[94]), "+f"(d[95]), "+f"(d[96]), "+f"(d[97]), "+f"(d[98]), "+f"(d[99]), "+f"(d[100]), "+f"(d[101]), "+f"(d[102]), "+f"(d[103]), "+f"(d[104]), "+f"(d[105]), "+f"(d[106]), "+f"(d[107]), "+f"(d[108]), "+f"(d[109]), "+f"(d[110]), "+f"(d[111]), "+f"(d[112]), "+f"(d[113]), "+f"(d[114]), "+f"(d[115]), "+f"(d[116]), "+f"(d[117]), "+f"(d[118]), "+f"(d[119]), "+f"(d[120]), "+f"(d[121]), "+f"(d[122]), "+f"(d[123]), "+f"(d[124]), "+f"(d[125]), "+f"(d[126]), "+f"(d[127])
    : "r"(da), "r"(db));
  }
}
template<bool INIT> __device__ __forceinline__ void wgmma_n128_ss(float* d, uint32_t da, uint32_t db) {
  if constexpr (INIT) {
  asm volatile("{\n.reg .pred p;\n.reg .b64 da, db;\nsetp.ne.b32 p, 0, 0;\nmov.b64 da, {%64, 0x40000040};\nmov.b64 db, {%65, 0x40000040};\nwgmma.mma_async.sync.aligned.m64n128k16.f32.bf16.bf16 {%0, %1, %2, %3, %4, %5, %6, %7, %8, %9, %10, %11, %12, %13, %14, %15, %16, %17, %18, %19, %20, %21, %22, %23, %24, %25, %26, %27, %28, %29, %30, %31, %32, %33, %34, %35, %36, %37, %38, %39, %40, %41, %42, %43, %44, %45, %46, %47, %48, %49, %50, %51, %52, %53, %54, %55, %56, %57, %58, %59, %60, %61, %62, %63}, da, db, p, 1, 1, 0, 1;\n}\n"
    : "=f"(d[0]), "=f"(d[1]), "=f"(d[2]), "=f"(d[3]), "=f"(d[4]), "=f"(d[5]), "=f"(d[6]), "=f"(d[7]), "=f"(d[8]), "=f"(d[9]), "=f"(d[10]), "=f"(d[11]), "=f"(d[12]), "=f"(d[13]), "=f"(d[14]), "=f"(d[15]), "=f"(d[16]), "=f"(d[17]), "=f"(d[18]), "=f"(d[19]), "=f"(d[20]), "=f"(d[21]), "=f"(d[22]), "=f"(d[23]), "=f"(d[24]), "=f"(d[25]), "=f"(d[26]), "=f"(d[27]), "=f"(d[28]), "=f"(d[29]), "=f"(d[30]), "=f"(d[31]), "=f"(d[32]), "=f"(d[33]), "=f"(d[34]), "=f"(d[35]), "=f"(d[36]), "=f"(d[37]), "=f"(d[38]), "=f"(d[39]), "=f"(d[40]), "=f"(d[41]), "=f"(d[42]), "=f"(d[43]), "=f"(d[44]), "=f"(d[45]), "=f"(d[46]), "=f"(d[47]), "=f"(d[48]), "=f"(d[49]), "=f"(d[50]), "=f"(d[51]), "=f"(d[52]), "=f"(d[53]), "=f"(d[54]), "=f"(d[55]), "=f"(d[56]), "=f"(d[57]), "=f"(d[58]), "=f"(d[59]), "=f"(d[60]), "=f"(d[61]), "=f"(d[62]), "=f"(d[63])
    : "r"(da), "r"(db));
  } else {
  asm volatile("{\n.reg .pred p;\n.reg .b64 da, db;\nsetp.ne.b32 p, 1, 0;\nmov.b64 da, {%64, 0x40000040};\nmov.b64 db, {%65, 0x40000040};\nwgmma.mma_async.sync.aligned.m64n128k16.f32.bf16.bf16 {%0, %1, %2, %3, %4, %5, %6, %7, %8, %9, %10, %11, %12, %13, %14, %15, %16, %17, %18, %19, %20, %21, %22, %23, %24, %25, %26, %27, %28, %29, %30, %31, %32, %33, %34, %35, %36, %37, %38, %39, %40, %41, %42, %43, %44, %45, %46, %47, %48, %49, %50, %51, %52, %53, %54, %55, %56, %57, %58, %59, %60, %61, %62, %63}, da, db, p, 1, 1, 0, 1;\n}\n"
    : "+f"(d[0]), "+f"(d[1]), "+f"(d[2]), "+f"(d[3]), "+f"(d[4]), "+f"(d[5]), "+f"(d[6]), "+f"(d[7]), "+f"(d[8]), "+f"(d[9]), "+f"(d[10]), "+f"(d[11]), "+f"(d[12]), "+f"(d[13]), "+f"(d[14]), "+f"(d[15]), "+f"(d[16]), "+f"(d[17]), "+f"(d[18]), "+f"(d[19]), "+f"(d[20]), "+f"(d[21]), "+f"(d[22]), "+f"(d[23]), "+f"(d[24]), "+f"(d[25]), "+f"(d[26]), "+f"(d[27]), "+f"(d[28]), "+f"(d[29]), "+f"(d[30]), "+f"(d[31]), "+f"(d[32]), "+f"(d[33]), "+f"(d[34]), "+f"(d[35]), "+f"(d[36]), "+f"(d[37]), "+f"(d[38]), "+f"(d[39]), "+f"(d[40]), "+f"(d[41]), "+f"(d[42]), "+f"(d[43]), "+f"(d[44]), "+f"(d[45]), "+f"(d[46]), "+f"(d[47]), "+f"(d[48]), "+f"(d[49]), "+f"(d[50]), "+f"(d[51]), "+f"(d[52]), "+f"(d[53]), "+f"(d[54]), "+f"(d[55]), "+f"(d[56]), "+f"(d[57]), "+f"(d[58]), "+f"(d[59]), "+f"(d[60]), "+f"(d[61]), "+f"(d[62]), "+f"(d[63])
    : "r"(da), "r"(db));
  }
}
template<bool INIT> __device__ __forceinline__ void wgmma_n256_rs(float* d, const uint32_t* a, uint32_t db) {
  if constexpr (INIT) {
  asm volatile("{\n.reg .pred p;\n.reg .b64 db;\nsetp.ne.b32 p, 0, 0;\nmov.b64 db, {%132, 0x40000040};\nwgmma.mma_async.sync.aligned.m64n256k16.f32.bf16.bf16 {%0, %1, %2, %3, %4, %5, %6, %7, %8, %9, %10, %11, %12, %13, %14, %15, %16, %17, %18, %19, %20, %21, %22, %23, %24, %25, %26, %27, %28, %29, %30, %31, %32, %33, %34, %35, %36, %37, %38, %39, %40, %41, %42, %43, %44, %45, %46, %47, %48, %49, %50, %51, %52, %53, %54, %55, %56, %57, %58, %59, %60, %61, %62, %63, %64, %65, %66, %67, %68, %69, %70, %71, %72, %73, %74, %75, %76, %77, %78, %79, %80, %81, %82, %83, %84, %85, %86, %87, %88, %89, %90, %91, %92, %93, %94, %95, %96, %97, %98, %99, %100, %101, %102, %103, %104, %105, %106, %107, %108, %109, %110, %111, %112, %113, %114, %115, %116, %117, %118, %119, %120, %121, %122, %123, %124, %125, %126, %127}, {%128, %129, %130, %131}, db, p, 1, 1, 1;\n}\n"
    : "=f"(d[0]), "=f"(d[1]), "=f"(d[2]), "=f"(d[3]), "=f"(d[4]), "=f"(d[5]), "=f"(d[6]), "=f"(d[7]), "=f"(d[8]), "=f"(d[9]), "=f"(d[10]), "=f"(d[11]), "=f"(d[12]), "=f"(d[13]), "=f"(d[14]), "=f"(d[15]), "=f"(d[16]), "=f"(d[17]), "=f"(d[18]), "=f"(d[19]), "=f"(d[20]), "=f"(d[21]), "=f"(d[22]), "=f"(d[23]), "=f"(d[24]), "=f"(d[25]), "=f"(d[26]), "=f"(d[27]), "=f"(d[28]), "=f"(d[29]), "=f"(d[30]), "=f"(d[31]), "=f"(d[32]), "=f"(d[33]), "=f"(d[34]), "=f"(d[35]), "=f"(d[36]), "=f"(d[37]), "=f"(d[38]), "=f"(d[39]), "=f"(d[40]), "=f"(d[41]), "=f"(d[42]), "=f"(d[43]), "=f"(d[44]), "=f"(d[45]), "=f"(d[46]), "=f"(d[47]), "=f"(d[48]), "=f"(d[49]), "=f"(d[50]), "=f"(d[51]), "=f"(d[52]), "=f"(d[53]), "=f"(d[54]), "=f"(d[55]), "=f"(d[56]), "=f"(d[57]), "=f"(d[58]), "=f"(d[59]), "=f"(d[60]), "=f"(d[61]), "=f"(d[62]), "=f"(d[63]), "=f"(d[64]), "=f"(d[65]), "=f"(d[66]), "=f"(d[67]), "=f"(d[68]), "=f"(d[69]), "=f"(d[70]), "=f"(d[71]), "=f"(d[72]), "=f"(d[73]), "=f"(d[74]), "=f"(d[75]), "=f"(d[76]), "=f"(d[77]), "=f"(d[78]), "=f"(d[79]), "=f"(d[80]), "=f"(d[81]), "=f"(d[82]), "=f"(d[83]), "=f"(d[84]), "=f"(d[85]), "=f"(d[86]), "=f"(d[87]), "=f"(d[88]), "=f"(d[89]), "=f"(d[90]), "=f"(d[91]), "=f"(d[92]), "=f"(d[93]), "=f"(d[94]), "=f"(d[95]), "=f"(d[96]), "=f"(d[97]), "=f"(d[98]), "=f"(d[99]), "=f"(d[100]), "=f"(d[101]), "=f"(d[102]), "=f"(d[103]), "=f"(d[104]), "=f"(d[105]), "=f"(d[106]), "=f"(d[107]), "=f"(d[108]), "=f"(d[109]), "=f"(d[110]), "=f"(d[111]), "=f"(d[112]), "=f"(d[113]), "=f"(d[114]), "=f"(d[115]), "=f"(d[116]), "=f"(d[117]), "=f"(d[118]), "=f"(d[119]), "=f"(d[120]), "=f"(d[121]), "=f"(d[122]), "=f"(d[123]), "=f"(d[124]), "=f"(d[125]), "=f"(d[126]), "=f"(d[127])
    : "r"(a[0]), "r"(a[1]), "r"(a[2]), "r"(a[3]), "r"(db));
  } else {
  asm volatile("{\n.reg .pred p;\n.reg .b64 db;\nsetp.ne.b32 p, 1, 0;\nmov.b64 db, {%132, 0x40000040};\nwgmma.mma_async.sync.aligned.m64n256k16.f32.bf16.bf16 {%0, %1, %2, %3, %4, %5, %6, %7, %8, %9, %10, %11, %12, %13, %14, %15, %16, %17, %18, %19, %20, %21, %22, %23, %24, %25, %26, %27, %28, %29, %30, %31, %32, %33, %34, %35, %36, %37, %38, %39, %40, %41, %42, %43, %44, %45, %46, %47, %48, %49, %50, %51, %52, %53, %54, %55, %56, %57, %58, %59, %60, %61, %62, %63, %64, %65, %66, %67, %68, %69, %70, %71, %72, %73, %74, %75, %76, %77, %78, %79, %80, %81, %82, %83, %84, %85, %86, %87, %88, %89, %90, %91, %92, %93, %94, %95, %96, %97, %98, %99, %100, %101, %102, %103, %104, %105, %106, %107, %108, %109, %110, %111, %112, %113, %114, %115, %116, %117, %118, %119, %120, %121, %122, %123, %124, %125, %126, %127}, {%128, %129, %130, %131}, db, p, 1, 1, 1;\n}\n"
    : "+f"(d[0]), "+f"(d[1]), "+f"(d[2]), "+f"(d[3]), "+f"(d[4]), "+f"(d[5]), "+f"(d[6]), "+f"(d[7]), "+f"(d[8]), "+f"(d[9]), "+f"(d[10]), "+f"(d[11]), "+f"(d[12]), "+f"(d[13]), "+f"(d[14]), "+f"(d[15]), "+f"(d[16]), "+f"(d[17]), "+f"(d[18]), "+f"(d[19]), "+f"(d[20]), "+f"(d[21]), "+f"(d[22]), "+f"(d[23]), "+f"(d[24]), "+f"(d[25]), "+f"(d[26]), "+f"(d[27]), "+f"(d[28]), "+f"(d[29]), "+f"(d[30]), "+f"(d[31]), "+f"(d[32]), "+f"(d[33]), "+f"(d[34]), "+f"(d[35]), "+f"(d[36]), "+f"(d[37]), "+f"(d[38]), "+f"(d[39]), "+f"(d[40]), "+f"(d[41]), "+f"(d[42]), "+f"(d[43]), "+f"(d[44]), "+f"(d[45]), "+f"(d[46]), "+f"(d[47]), "+f"(d[48]), "+f"(d[49]), "+f"(d[50]), "+f"(d[51]), "+f"(d[52]), "+f"(d[53]), "+f"(d[54]), "+f"(d[55]), "+f"(d[56]), "+f"(d[57]), "+f"(d[58]), "+f"(d[59]), "+f"(d[60]), "+f"(d[61]), "+f"(d[62]), "+f"(d[63]), "+f"(d[64]), "+f"(d[65]), "+f"(d[66]), "+f"(d[67]), "+f"(d[68]), "+f"(d[69]), "+f"(d[70]), "+f"(d[71]), "+f"(d[72]), "+f"(d[73]), "+f"(d[74]), "+f"(d[75]), "+f"(d[76]), "+f"(d[77]), "+f"(d[78]), "+f"(d[79]), "+f"(d[80]), "+f"(d[81]), "+f"(d[82]), "+f"(d[83]), "+f"(d[84]), "+f"(d[85]), "+f"(d[86]), "+f"(d[87]), "+f"(d[88]), "+f"(d[89]), "+f"(d[90]), "+f"(d[91]), "+f"(d[92]), "+f"(d[93]), "+f"(d[94]), "+f"(d[95]), "+f"(d[96]), "+f"(d[97]), "+f"(d[98]), "+f"(d[99]), "+f"(d[100]), "+f"(d[101]), "+f"(d[102]), "+f"(d[103]), "+f"(d[104]), "+f"(d[105]), "+f"(d[106]), "+f"(d[107]), "+f"(d[108]), "+f"(d[109]), "+f"(d[110]), "+f"(d[111]), "+f"(d[112]), "+f"(d[113]), "+f"(d[114]), "+f"(d[115]), "+f"(d[116]), "+f"(d[117]), "+f"(d[118]), "+f"(d[119]), "+f"(d[120]), "+f"(d[121]), "+f"(d[122]), "+f"(d[123]), "+f"(d[124]), "+f"(d[125]), "+f"(d[126]), "+f"(d[127])
    : "r"(a[0]), "r"(a[1]), "r"(a[2]), "r"(a[3]), "r"(db));
  }
}
template<bool INIT> __device__ __forceinline__ void wgmma_n128_rs(float* d, const uint32_t* a, uint32_t db) {
  if constexpr (INIT) {
  asm volatile("{\n.reg .pred p;\n.reg .b64 db;\nsetp.ne.b32 p, 0, 0;\nmov.b64 db, {%68, 0x40000040};\nwgmma.mma_async.sync.aligned.m64n128k16.f32.bf16.bf16 {%0, %1, %2, %3, %4, %5, %6, %7, %8, %9, %10, %11, %12, %13, %14, %15, %16, %17, %18, %19, %20, %21, %22, %23, %24, %25, %26, %27, %28, %29, %30, %31, %32, %33, %34, %35, %36, %37, %38, %39, %40, %41, %42, %43, %44, %45, %46, %47, %48, %49, %50, %51, %52, %53, %54, %55, %56, %57, %58, %59, %60, %61, %62, %63}, {%64, %65, %66, %67}, db, p, 1, 1, 1;\n}\n"
    : "=f"(d[0]), "=f"(d[1]), "=f"(d[2]), "=f"(d[3]), "=f"(d[4]), "=f"(d[5]), "=f"(d[6]), "=f"(d[7]), "=f"(d[8]), "=f"(d[9]), "=f"(d[10]), "=f"(d[11]), "=f"(d[12]), "=f"(d[13]), "=f"(d[14]), "=f"(d[15]), "=f"(d[16]), "=f"(d[17]), "=f"(d[18]), "=f"(d[19]), "=f"(d[20]), "=f"(d[21]), "=f"(d[22]), "=f"(d[23]), "=f"(d[24]), "=f"(d[25]), "=f"(d[26]), "=f"(d[27]), "=f"(d[28]), "=f"(d[29]), "=f"(d[30]), "=f"(d[31]), "=f"(d[32]), "=f"(d[33]), "=f"(d[34]), "=f"(d[35]), "=f"(d[36]), "=f"(d[37]), "=f"(d[38]), "=f"(d[39]), "=f"(d[40]), "=f"(d[41]), "=f"(d[42]), "=f"(d[43]), "=f"(d[44]), "=f"(d[45]), "=f"(d[46]), "=f"(d[47]), "=f"(d[48]), "=f"(d[49]), "=f"(d[50]), "=f"(d[51]), "=f"(d[52]), "=f"(d[53]), "=f"(d[54]), "=f"(d[55]), "=f"(d[56]), "=f"(d[57]), "=f"(d[58]), "=f"(d[59]), "=f"(d[60]), "=f"(d[61]), "=f"(d[62]), "=f"(d[63])
    : "r"(a[0]), "r"(a[1]), "r"(a[2]), "r"(a[3]), "r"(db));
  } else {
  asm volatile("{\n.reg .pred p;\n.reg .b64 db;\nsetp.ne.b32 p, 1, 0;\nmov.b64 db, {%68, 0x40000040};\nwgmma.mma_async.sync.aligned.m64n128k16.f32.bf16.bf16 {%0, %1, %2, %3, %4, %5, %6, %7, %8, %9, %10, %11, %12, %13, %14, %15, %16, %17, %18, %19, %20, %21, %22, %23, %24, %25, %26, %27, %28, %29, %30, %31, %32, %33, %34, %35, %36, %37, %38, %39, %40, %41, %42, %43, %44, %45, %46, %47, %48, %49, %50, %51, %52, %53, %54, %55, %56, %57, %58, %59, %60, %61, %62, %63}, {%64, %65, %66, %67}, db, p, 1, 1, 1;\n}\n"
    : "+f"(d[0]), "+f"(d[1]), "+f"(d[2]), "+f"(d[3]), "+f"(d[4]), "+f"(d[5]), "+f"(d[6]), "+f"(d[7]), "+f"(d[8]), "+f"(d[9]), "+f"(d[10]), "+f"(d[11]), "+f"(d[12]), "+f"(d[13]), "+f"(d[14]), "+f"(d[15]), "+f"(d[16]), "+f"(d[17]), "+f"(d[18]), "+f"(d[19]), "+f"(d[20]), "+f"(d[21]), "+f"(d[22]), "+f"(d[23]), "+f"(d[24]), "+f"(d[25]), "+f"(d[26]), "+f"(d[27]), "+f"(d[28]), "+f"(d[29]), "+f"(d[30]), "+f"(d[31]), "+f"(d[32]), "+f"(d[33]), "+f"(d[34]), "+f"(d[35]), "+f"(d[36]), "+f"(d[37]), "+f"(d[38]), "+f"(d[39]), "+f"(d[40]), "+f"(d[41]), "+f"(d[42]), "+f"(d[43]), "+f"(d[44]), "+f"(d[45]), "+f"(d[46]), "+f"(d[47]), "+f"(d[48]), "+f"(d[49]), "+f"(d[50]), "+f"(d[51]), "+f"(d[52]), "+f"(d[53]), "+f"(d[54]), "+f"(d[55]), "+f"(d[56]), "+f"(d[57]), "+f"(d[58]), "+f"(d[59]), "+f"(d[60]), "+f"(d[61]), "+f"(d[62]), "+f"(d[63])
    : "r"(a[0]), "r"(a[1]), "r"(a[2]), "r"(a[3]), "r"(db));
  }
}
template<bool INIT> __device__ __forceinline__ void wgmma_n64_tt(float* d, uint32_t da, uint32_t db) {
  if constexpr (INIT) {
  asm volatile("{\n.reg .pred p;\n.reg .b64 da, db;\nsetp.ne.b32 p, 0, 0;\nmov.b64 da, {%32, 0x40000040};\nmov.b64 db, {%33, 0x40000040};\nwgmma.mma_async.sync.aligned.m64n64k16.f32.bf16.bf16 {%0, %1, %2, %3, %4, %5, %6, %7, %8, %9, %10, %11, %12, %13, %14, %15, %16, %17, %18, %19, %20, %21, %22, %23, %24, %25, %26, %27, %28, %29, %30, %31}, da, db, p, 1, 1, 1, 1;\n}\n"
    : "=f"(d[0]), "=f"(d[1]), "=f"(d[2]), "=f"(d[3]), "=f"(d[4]), "=f"(d[5]), "=f"(d[6]), "=f"(d[7]), "=f"(d[8]), "=f"(d[9]), "=f"(d[10]), "=f"(d[11]), "=f"(d[12]), "=f"(d[13]), "=f"(d[14]), "=f"(d[15]), "=f"(d[16]), "=f"(d[17]), "=f"(d[18]), "=f"(d[19]), "=f"(d[20]), "=f"(d[21]), "=f"(d[22]), "=f"(d[23]), "=f"(d[24]), "=f"(d[25]), "=f"(d[26]), "=f"(d[27]), "=f"(d[28]), "=f"(d[29]), "=f"(d[30]), "=f"(d[31])
    : "r"(da), "r"(db));
  } else {
  asm volatile("{\n.reg .pred p;\n.reg .b64 da, db;\nsetp.ne.b32 p, 1, 0;\nmov.b64 da, {%32, 0x40000040};\nmov.b64 db, {%33, 0x40000040};\nwgmma.mma_async.sync.aligned.m64n64k16.f32.bf16.bf16 {%0, %1, %2, %3, %4, %5, %6, %7, %8, %9, %10, %11, %12, %13, %14, %15, %16, %17, %18, %19, %20, %21, %22, %23, %24, %25, %26, %27, %28, %29, %30, %31}, da, db, p, 1, 1, 1, 1;\n}\n"
    : "+f"(d[0]), "+f"(d[1]), "+f"(d[2]), "+f"(d[3]), "+f"(d[4]), "+f"(d[5]), "+f"(d[6]), "+f"(d[7]), "+f"(d[8]), "+f"(d[9]), "+f"(d[10]), "+f"(d[11]), "+f"(d[12]), "+f"(d[13]), "+f"(d[14]), "+f"(d[15]), "+f"(d[16]), "+f"(d[17]), "+f"(d[18]), "+f"(d[19]), "+f"(d[20]), "+f"(d[21]), "+f"(d[22]), "+f"(d[23]), "+f"(d[24]), "+f"(d[25]), "+f"(d[26]), "+f"(d[27]), "+f"(d[28]), "+f"(d[29]), "+f"(d[30]), "+f"(d[31])
    : "r"(da), "r"(db));
  }
}
template<bool INIT> __device__ __forceinline__ void wgmma_n8_tn(float* d, uint32_t da, uint32_t db) {
  if constexpr (INIT) {
  asm volatile("{\n.reg .pred p;\n.reg .b64 da, db;\nsetp.ne.b32 p, 0, 0;\nmov.b64 da, {%4, 0x40000040};\nmov.b64 db, {%5, 8};\nwgmma.mma_async.sync.aligned.m64n8k16.f32.bf16.bf16 {%0, %1, %2, %3}, da, db, p, 1, 1, 1, 0;\n}\n"
    : "=f"(d[0]), "=f"(d[1]), "=f"(d[2]), "=f"(d[3])
    : "r"(da), "r"(db));
  } else {
  asm volatile("{\n.reg .pred p;\n.reg .b64 da, db;\nsetp.ne.b32 p, 1, 0;\nmov.b64 da, {%4, 0x40000040};\nmov.b64 db, {%5, 8};\nwgmma.mma_async.sync.aligned.m64n8k16.f32.bf16.bf16 {%0, %1, %2, %3}, da, db, p, 1, 1, 1, 0;\n}\n"
    : "+f"(d[0]), "+f"(d[1]), "+f"(d[2]), "+f"(d[3])
    : "r"(da), "r"(db));
  }
}
template<bool INIT> __device__ __forceinline__ void wgmma_n40_rs(float* d, const uint32_t* a, uint32_t db) {
  if constexpr (INIT) {
  asm volatile("{\n.reg .pred p;\n.reg .b64 db;\nsetp.ne.b32 p, 0, 0;\nmov.b64 db, {%24, 0x40000040};\nwgmma.mma_async.sync.aligned.m64n40k16.f32.bf16.bf16 {%0, %1, %2, %3, %4, %5, %6, %7, %8, %9, %10, %11, %12, %13, %14, %15, %16, %17, %18, %19}, {%20, %21, %22, %23}, db, p, 1, 1, 1;\n}\n"
    : "=f"(d[0]), "=f"(d[1]), "=f"(d[2]), "=f"(d[3]), "=f"(d[4]), "=f"(d[5]), "=f"(d[6]), "=f"(d[7]), "=f"(d[8]), "=f"(d[9]), "=f"(d[10]), "=f"(d[11]), "=f"(d[12]), "=f"(d[13]), "=f"(d[14]), "=f"(d[15]), "=f"(d[16]), "=f"(d[17]), "=f"(d[18]), "=f"(d[19])
    : "r"(a[0]), "r"(a[1]), "r"(a[2]), "r"(a[3]), "r"(db));
  } else {
  asm volatile("{\n.reg .pred p;\n.reg .b64 db;\nsetp.ne.b32 p, 1, 0;\nmov.b64 db, {%24, 0x40000040};\nwgmma.mma_async.sync.aligned.m64n40k16.f32.bf16.bf16 {%0, %1, %2, %3, %4, %5, %6, %7, %8, %9, %10, %11, %12, %13, %14, %15, %16, %17, %18, %19}, {%20, %21, %22, %23}, db, p, 1, 1, 1;\n}\n"
    : "+f"(d[0]), "+f"(d[1]), "+f"(d[2]), "+f"(d[3]), "+f"(d[4]), "+f"(d[5]), "+f"(d[6]), "+f"(d[7]), "+f"(d[8]), "+f"(d[9]), "+f"(d[10]), "+f"(d[11]), "+f"(d[12]), "+f"(d[13]), "+f"(d[14]), "+f"(d[15]), "+f"(d[16]), "+f"(d[17]), "+f"(d[18]), "+f"(d[19])
    : "r"(a[0]), "r"(a[1]), "r"(a[2]), "r"(a[3]), "r"(db));
  }
}

__device__ __forceinline__ void quad_transpose(uint32_t& r0, uint32_t& r1, uint32_t& r2, uint32_t& r3, int c) {
  bool o1 = c & 1, o2 = c & 2;
  uint32_t t0 = o1 ? r0 : r1, t1 = o1 ? r2 : r3;
  t0 = __shfl_xor_sync(~0u, t0, 1); t1 = __shfl_xor_sync(~0u, t1, 1);
  if (o1) { r0 = t0; r2 = t1; } else { r1 = t0; r3 = t1; }
  t0 = o2 ? r0 : r2; t1 = o2 ? r1 : r3;
  t0 = __shfl_xor_sync(~0u, t0, 2); t1 = __shfl_xor_sync(~0u, t1, 2);
  if (o2) { r0 = t0; r1 = t1; } else { r2 = t0; r3 = t1; }
}

__device__ __forceinline__ bool own_tile(int T) { return (0x0D0Du >> T) & 1; }
__device__ __forceinline__ bool wide_tile(int T) { return (0x3939u >> T) & 1; }

template<int V> struct IntC { static constexpr int value = V; };

__device__ __forceinline__ const CUtensorMap* tile_info(const Params& prm, int T, int j, int rank, int& col) {
  const int tile = T & 7;
  col = 128 * j + 64 * rank;
  if (tile == 0) col = 1024 + 1024 * rank + 128 * j;
  if (tile < 2) return T < 8 ? &prm.wqkv_n : &prm.wqkv_p;
  if (tile == 2) return &prm.wo_p;
  if (tile == 7) return &prm.wd_p;
  col = 448 * j + 128 * (tile - 3);
  return rank ? &prm.wu_p : &prm.wg_p;
}

__device__ __forceinline__ void finish_stats(float4 a, float4 b, float& mean0, float& rstd0, float& mean1, float& rstd1) {
  float ma = a.x + a.z, mb = b.x + b.z;
  ma += __shfl_xor_sync(~0u, ma, 1); mb += __shfl_xor_sync(~0u, mb, 1);
  ma += __shfl_xor_sync(~0u, ma, 2); mb += __shfl_xor_sync(~0u, mb, 2);
  ma *= 0.125f; mb *= 0.125f;
  float va = a.y + a.w + 128.f * ((a.x - ma) * (a.x - ma) + (a.z - ma) * (a.z - ma));
  float vb = b.y + b.w + 128.f * ((b.x - mb) * (b.x - mb) + (b.z - mb) * (b.z - mb));
  va += __shfl_xor_sync(~0u, va, 1); vb += __shfl_xor_sync(~0u, vb, 1);
  va += __shfl_xor_sync(~0u, va, 2); vb += __shfl_xor_sync(~0u, vb, 2);
  mean0 = ma; mean1 = mb;
  rstd0 = rsqrtf(va * (1.f / 1024.f) + 1e-5f); rstd1 = rsqrtf(vb * (1.f / 1024.f) + 1e-5f);
}
__device__ __forceinline__ void tile_stats(const uint32_t* P, float2 (*st)[8], int row, int j, int c) {
  const float p0 = bf_lo(__shfl_sync(~0u, P[0], 0, 4)), p1 = bf_lo(__shfl_sync(~0u, P[1], 0, 4));
  float s0 = 0.f, s1 = 0.f, q0 = 0.f, q1 = 0.f;
#pragma unroll
  for (int b = 0; b < 16; b++) {
    float a0 = bf_lo(P[2 * b]) - p0, a1 = bf_hi(P[2 * b]) - p0, b0 = bf_lo(P[2 * b + 1]) - p1, b1 = bf_hi(P[2 * b + 1]) - p1;
    s0 += a0 + a1; s1 += b0 + b1;
    q0 = fmaf(a0, a0, fmaf(a1, a1, q0)); q1 = fmaf(b0, b0, fmaf(b1, b1, q1));
  }
  s0 += __shfl_xor_sync(~0u, s0, 1); s1 += __shfl_xor_sync(~0u, s1, 1);
  q0 += __shfl_xor_sync(~0u, q0, 1); q1 += __shfl_xor_sync(~0u, q1, 1);
  s0 += __shfl_xor_sync(~0u, s0, 2); s1 += __shfl_xor_sync(~0u, s1, 2);
  q0 += __shfl_xor_sync(~0u, q0, 2); q1 += __shfl_xor_sync(~0u, q1, 2);
  st_f2_if(&st[row][j], p0 + s0 * (1.f / 128.f), fmaxf(q0 - s0 * s0 * (1.f / 128.f), 0.f), c == 0);
  st_f2_if(&st[row + 8][j], p1 + s1 * (1.f / 128.f), fmaxf(q1 - s1 * s1 * (1.f / 128.f), 0.f), c == 0);
}

__device__ __forceinline__ void store_img(uint8_t* img, const uint32_t* P, uint32_t ioff) {
#pragma unroll
  for (int gi = 0; gi < 4; gi++) {
    uint8_t* p = img + (gi >> 1) * SLOT + (ioff ^ ((gi & 1) * 64));
    *(uint4*)p = make_uint4(P[8 * gi], P[8 * gi + 2], P[8 * gi + 4], P[8 * gi + 6]);
    *(uint4*)(p + 1024) = make_uint4(P[8 * gi + 1], P[8 * gi + 3], P[8 * gi + 5], P[8 * gi + 7]);
  }
}

__device__ __forceinline__ void pack_half(const float* acc, uint32_t* PK, uint32_t cs_addr, float mean0, float mean1) {
#pragma unroll
  for (int b = 0; b < 16; b++) {
    float2 cs = lds_f2(cs_addr + b * 32);
    const int o = ((b >> 2) & 1) * 16 + (b >> 3) * 4 + (b & 3);
    PK[o] = pack_bf16(fmaf(-mean0, cs.x, acc[4 * b]), fmaf(-mean0, cs.y, acc[4 * b + 1]));
    PK[o + 8] = pack_bf16(fmaf(-mean1, cs.x, acc[4 * b + 2]), fmaf(-mean1, cs.y, acc[4 * b + 3]));
  }
}
__device__ __forceinline__ void pick_unit(uint32_t* t, const uint32_t* PK, int u) {
#define PICK(U) case U: asm volatile("mov.b32 %0, %8;\nmov.b32 %1, %9;\nmov.b32 %2, %10;\nmov.b32 %3, %11;\nmov.b32 %4, %12;\nmov.b32 %5, %13;\nmov.b32 %6, %14;\nmov.b32 %7, %15;" \
    : "=r"(t[0]), "=r"(t[1]), "=r"(t[2]), "=r"(t[3]), "=r"(t[4]), "=r"(t[5]), "=r"(t[6]), "=r"(t[7]) \
    : "r"(PK[8 * U]), "r"(PK[8 * U + 1]), "r"(PK[8 * U + 2]), "r"(PK[8 * U + 3]), "r"(PK[8 * U + 4]), "r"(PK[8 * U + 5]), "r"(PK[8 * U + 6]), "r"(PK[8 * U + 7])); break;
  switch (u) { PICK(0) PICK(1) PICK(2) PICK(3) PICK(4) PICK(5) PICK(6) default: PICK(7) }
#undef PICK
}
__device__ __forceinline__ void load_img(const uint8_t* img, uint32_t* R, uint32_t ioff) {
#pragma unroll
  for (int gi = 0; gi < 4; gi++) {
    const uint8_t* p = img + (gi >> 1) * SLOT + (ioff ^ ((gi & 1) * 64));
    uint4 a = __ldcg((const uint4*)p), b = __ldcg((const uint4*)(p + 1024));
    R[8 * gi] = a.x; R[8 * gi + 1] = a.y; R[8 * gi + 2] = a.z; R[8 * gi + 3] = a.w;
    R[8 * gi + 4] = b.x; R[8 * gi + 5] = b.y; R[8 * gi + 6] = b.z; R[8 * gi + 7] = b.w;
  }
}
__device__ __forceinline__ void load_plain(const __nv_bfloat16* p, uint32_t* P) {
#pragma unroll
  for (int gi = 0; gi < 4; gi++) {
    uint4 a = __ldg((const uint4*)(p + 32 * gi)), b = __ldg((const uint4*)(p + 32 * gi + 8 * D_));
    P[8 * gi] = a.x; P[8 * gi + 2] = a.y; P[8 * gi + 4] = a.z; P[8 * gi + 6] = a.w;
    P[8 * gi + 1] = b.x; P[8 * gi + 3] = b.y; P[8 * gi + 5] = b.z; P[8 * gi + 7] = b.w;
  }
}
__device__ __forceinline__ void transpose_all(uint32_t* P, int c) {
#pragma unroll
  for (int gi = 0; gi < 4; gi++) {
    quad_transpose(P[8 * gi], P[8 * gi + 2], P[8 * gi + 4], P[8 * gi + 6], c);
    quad_transpose(P[8 * gi + 1], P[8 * gi + 3], P[8 * gi + 5], P[8 * gi + 7], c);
  }
}
__device__ __forceinline__ void add_residual(uint32_t* P, const uint32_t* R, const float* acc) {
#pragma unroll
  for (int b = 0; b < 16; b++) {
    const uint32_t r0 = R[(b >> 2) * 8 + (b & 3)], r1 = R[(b >> 2) * 8 + 4 + (b & 3)];
    P[2 * b] = pack_bf16(bf_lo(r0) + acc[4 * b], bf_hi(r0) + acc[4 * b + 1]);
    P[2 * b + 1] = pack_bf16(bf_lo(r1) + acc[4 * b + 2], bf_hi(r1) + acc[4 * b + 3]);
  }
}
__device__ __forceinline__ float phi_s(float raw, float rstd, float rl2) { return fmaxf(fmaf(raw, rstd, 1e-6f), 1e-6f) + ex2f(fminf(raw * rl2, 0.f)); }
__device__ __forceinline__ uint32_t phi2(uint32_t p, float rstd, float rl2) { return pack_bf16(phi_s(bf_lo(p), rstd, rl2), phi_s(bf_hi(p), rstd, rl2)); }
__device__ __forceinline__ uint32_t scale2(uint32_t p, float rstd) { return pack_bf16(bf_lo(p) * rstd, bf_hi(p) * rstd); }

#define TR(i)

__global__ void __launch_bounds__(384, 1) fused_kernel(const __grid_constant__ Params prm) {
  extern __shared__ __align__(1024) uint8_t smem_raw[];
  const uint32_t sbase = __shfl_sync(~0u, smem_u32(smem_raw), 0);
  const uint32_t full = sbase + OFF_BAR, empty = full + 64;
  const uint32_t bar_kvdone = full + 128, bar_kvready = full + 136, bar_sig = full + 144;
  const uint32_t bar_csq = full + 160, bar_csgu = full + 168, bar_sig2 = full + 176;
  const int warp = __shfl_sync(~0u, threadIdx.x >> 5, 0), lane = threadIdx.x & 31;
  const int rank = blockIdx.x & 1;
  const bool helper = blockIdx.x < 4;
  const int ci = blockIdx.x >> 1, tq = ci - 4;
  const int mp = (ci < 4 || ci >= 64) ? 0 : (tq < 32 ? tq & 7 : 1 + (tq - 32) % 7);
  const int j = ci < 4 ? 2 + ci : ci >= 64 ? ci - 58 : (tq < 32 ? tq >> 3 : 4 + (tq - 32) / 7);
  const int m = mp * 2 + rank;
  const int cta = m * 8 + j;

  if (threadIdx.x < 24) {
    const int t = threadIdx.x;
    uint32_t cnt = t < 8 ? 2 : t < 16 ? 4 : t == 16 ? 8 : t == 17 ? 2 : t < 20 ? 4 : t < 22 ? 1 : 4;
    mbar_init(full + 8 * t, helper ? 1 : cnt);
    asm volatile("fence.mbarrier_init.release.cluster;" ::: "memory");
  }
  if (threadIdx.x >= 64 && threadIdx.x < 128) sts_u32(sbase + OFF_ONES + (threadIdx.x - 64) * 4, 0x3F803F80u);
  fence_async_smem();
  const uint32_t epoch = __ldcg(&g_epoch) + 1;
  cluster_sync();

  if (warp >= 4) {
    asm volatile("setmaxnreg.inc.sync.aligned.u32 232;");
    const int cw = (warp >> 2) - 1, w4 = warp & 3, g = lane >> 2, c = lane & 3;
    const bool relt = w4 == 0 && lane < 2;
    const uint32_t dones = make_desc(sbase + OFF_ONES, 128);
    if (!helper) {
      const int rloc = cw * 64 + w4 * 16 + g;
      const int row = m * 128 + rloc;
      const uint32_t ioff = rloc * 128 + ((c ^ g) << 4);
      const uint32_t tile_off = (m * 16 + 2 * j) * SLOT;
      const uint32_t da0 = make_desc(sbase + cw * 8192, 16), db0 = make_desc(sbase + SLOT, 8192);
      const uint32_t stg = sbase + OFF_STG + cw * 16384;
      const uint32_t rempty = mapa(empty, lane & 1);
      uint32_t n = 0, pos = 0;
      bool ok = false;
      uint32_t PK[64];
      float mean0, rstd0, mean1, rstd1;
      TR(0);
      load_plain(prm.xin + (size_t)row * D_ + 128 * j + 8 * c, PK);
      transpose_all(PK, c);
#pragma unroll 1
      for (int T = 0; T < 16; T++) {
        const int layer = T >> 3, tile = T & 7;
        const bool wide = wide_tile(T), own = own_tile(T);
        const int nsteps = tile == 7 ? 56 : 16;
        const bool lnin = tile == 0 || tile == 3;
        float2 (*st)[8] = g_stats[layer * 2 + (tile != 0)];
        if (tile == 3) { pos += 2048; if (pos >= NSLOT * 1024) pos -= NSLOT * 1024; }
        auto run = [&](auto WIDE_) {
          constexpr bool WIDE = decltype(WIDE_)::value;
          float acc[WIDE ? 128 : 64];
          auto kstep = [&](auto FIRST_, auto RS_, auto&& hook) {
            constexpr bool FIRST = decltype(FIRST_)::value;
            constexpr int RS = decltype(RS_)::value;
            if (!ok) mbar_wait(full + 8 * (n & 7), (n >> 3) & 1);
            const uint32_t da = da0 + pos, db = db0 + pos;
            n++;
            wgmma_fence();
#pragma unroll
            for (int kk = 0; kk < 4; kk++) {
              if (FIRST && kk == 0) {
                if constexpr (RS) { if constexpr (WIDE) wgmma_n256_rs<true>(acc, PK, db); else wgmma_n128_rs<true>(acc, PK, db); }
                else { if constexpr (WIDE) wgmma_n256_ss<true>(acc, da, db); else wgmma_n128_ss<true>(acc, da, db); }
              } else {
                if constexpr (RS) { if constexpr (WIDE) wgmma_n256_rs<false>(acc, PK + 16 * (RS - 1) + 4 * kk, db + kk * 128); else wgmma_n128_rs<false>(acc, PK + 16 * (RS - 1) + 4 * kk, db + kk * 128); }
                else { if constexpr (WIDE) wgmma_n256_ss<false>(acc, da + kk * 2, db + kk * 128); else wgmma_n128_ss<false>(acc, da + kk * 2, db + kk * 128); }
              }
              if (kk == 2) ok = mbar_test(full + 8 * (n & 7), (n >> 3) & 1);
              if (kk == 3) wgmma_commit();
              hook(kk);
            }
            pos += WIDE ? 3072 : 2048; if (pos >= NSLOT * 1024) pos -= NSLOT * 1024;
            if constexpr (!FIRST) {
              wgmma_wait<1>();
              mbar_arrive_remote_if(rempty + 8 * ((n - 2) & 7), relt);
            }
          };
          auto nohook = [](int) {};
          int i;
          if (own) {
            store_img((WIDE ? (tile == 0 ? g_x2 : g_x1) : g_o) + tile_off, PK, ioff);
            __syncwarp();
            mbar_arrive_if(bar_sig + 8 * cw, lane == 0);
            kstep(IntC<1>{}, IntC<1>{}, nohook);
            if constexpr (WIDE) {
              tile_stats(PK, st, row, j, c);
              __syncwarp();
              mbar_arrive_if(bar_sig2 + 8 * cw, lane == 0);
            }
            kstep(IntC<0>{}, IntC<2>{}, nohook);
            kstep(IntC<0>{}, IntC<0>{}, nohook);
            i = 3;
          } else {
            kstep(IntC<1>{}, IntC<0>{}, nohook);
            i = 1;
            uint32_t t[8];
            pick_unit(t, PK, 0);
            if (!WIDE && tile == 1) {
#pragma unroll 1
              for (int u = 0; u < 8; u++) {
                const float rstd = (u & 1) ? rstd1 : rstd0, rl2 = rstd * 1.4426950408889634f;
                const uint32_t ad = stg + (w4 * 16 + (u & 1) * 8 + (lane & 7)) * 128 + ((((u & 2) * 2 + (lane >> 3)) ^ (lane & 7)) << 4);
                kstep(IntC<0>{}, IntC<0>{}, [&](int q) { t[q] = phi2(t[q], rstd, rl2); t[4 + q] = scale2(t[4 + q], rstd); });
                stmatrix_x4(ad, t[0], t[1], t[2], t[3]);
                stmatrix_x4(ad + 8192, t[4], t[5], t[6], t[7]);
                pick_unit(t, PK, u + 1);
                i++;
                if ((u & 3) == 3) {
                  float kv[32], z[4];
                  fence_async_smem();
                  wg_bar(1 + cw);
                  const uint32_t da = make_desc(stg, 8192);
                  wgmma_fence();
                  wgmma_n64_tt<true>(kv, da, da + 512);
#pragma unroll
                  for (int kk = 1; kk < 4; kk++) wgmma_n64_tt<false>(kv, da + kk * 128, da + 512 + kk * 128);
                  wgmma_n8_tn<true>(z, da, dones);
#pragma unroll
                  for (int kk = 1; kk < 4; kk++) wgmma_n8_tn<false>(z, da + kk * 128, dones);
                  wgmma_commit();
                  kstep(IntC<0>{}, IntC<0>{}, nohook);
                  i++;
                  const bool hi = w4 >= 2;
                  float* dst = &g_kv[epoch & 1][layer][4 * j + (u >> 2) * 2 + (w4 >> 1)][0] + ((w4 & 1) * 16 + g) * 32 + c * 8;
                  float s[16];
#pragma unroll
                  for (int q = 0; q < 16; q++) s[q] = hi ? kv[16 + q] : kv[q];
                  red_add_v4(dst, s[0], s[1], s[4], s[5]);
                  red_add_v4(dst + 4, s[8], s[9], s[12], s[13]);
                  red_add_v4(dst + 256, s[2], s[3], s[6], s[7]);
                  red_add_v4(dst + 260, s[10], s[11], s[14], s[15]);
                  { float* zd = dst - ((w4 & 1) * 16 + g) * 31 + 1024; red_add_f32_if(zd, z[0], c == 0); red_add_f32_if(zd + 8, z[2], c == 0); }
                  wg_bar(1 + cw);
                  mbar_arrive_if(bar_kvdone, u == 7 && lane == 0);
                }
              }
            } else {
              const int nu = tile == 7 ? 4 : 8;
              uint8_t* hb = g_h + (m * 56 + (tile - 4) * 16 + (tile == 7 ? j : 2 * j)) * SLOT;
#pragma unroll 1
              for (int u = 0; u < nu; u++) {
                const float rstd = (u & 1) ? rstd1 : rstd0;
                const float ke = rstd * -1.4426950408889634f, iv = rcpf(rstd * rstd);
                kstep(IntC<0>{}, IntC<0>{}, [&](int q) {
                  float s0 = rcpf(fmaf(ex2f(bf_lo(t[q]) * ke), iv, iv)), s1 = rcpf(fmaf(ex2f(bf_hi(t[q]) * ke), iv, iv));
                  t[q] = hmul2(hmul2(t[q], t[4 + q]), pack_bf16(s0, s1));
                });
                *(uint4*)(hb + (u >> 2) * SLOT + (u & 1) * 1024 + (ioff ^ ((u & 2) * 32))) = make_uint4(t[0], t[1], t[2], t[3]);
                pick_unit(t, PK, u + 1);
                i++;
              }
              __syncwarp();
              mbar_arrive_if(bar_sig + 8 * cw, lane == 0);
            }
          }
          if (!WIDE && (tile == 2 || tile == 7)) load_img((tile == 2 ? g_x2 : g_x1) + tile_off, PK + 32, ioff);
#pragma unroll 1
          for (; i < nsteps; i++) {
            if (WIDE && i == 15 && lnin) {
              uint4 sa = __ldcg((const uint4*)&st[row][2 * c]), sb = __ldcg((const uint4*)&st[row + 8][2 * c]);
              PK[0] = sa.x; PK[1] = sa.y; PK[2] = sa.z; PK[3] = sa.w; PK[4] = sb.x; PK[5] = sb.y; PK[6] = sb.z; PK[7] = sb.w;
            }
            kstep(IntC<0>{}, IntC<0>{}, nohook);
          }
        if (WIDE && lnin) {
          finish_stats(make_float4(__uint_as_float(PK[0]), __uint_as_float(PK[1]), __uint_as_float(PK[2]), __uint_as_float(PK[3])),
                       make_float4(__uint_as_float(PK[4]), __uint_as_float(PK[5]), __uint_as_float(PK[6]), __uint_as_float(PK[7])), mean0, rstd0, mean1, rstd1);
          if (T != 8) mbar_wait(tile == 0 ? bar_csq : bar_csgu, layer);
        }
        wgmma_wait<0>();
        mbar_arrive_remote_if(rempty + 8 * ((n - 1) & 7), relt);
        TR(1 + 2 * T);
        if (!WIDE && (tile == 2 || tile == 7)) add_residual(PK, PK + 32, acc);
        else if (WIDE || tile != 1) {
          const uint32_t cs = (tile == 0 ? sbase + OFF_CSQ : sbase + OFF_CSGU + (tile - 3) * 1024) + 8 * c;
          pack_half(acc, PK, cs, mean0, mean1);
          if constexpr (WIDE) pack_half(acc + 64, PK + 32, cs + 512, mean0, mean1);
        } else {
#pragma unroll
          for (int b = 0; b < 16; b++) {
            float2 cs = lds_f2(sbase + OFF_CSQ + (256 + b * 8 + 2 * c) * 4);
            const float l0 = rstd0 * 1.4426950408889634f, l1 = rstd1 * 1.4426950408889634f;
            PK[32 + 2 * b] = pack_bf16(phi_s(fmaf(-mean0, cs.x, acc[4 * b]), rstd0, l0), phi_s(fmaf(-mean0, cs.y, acc[4 * b + 1]), rstd0, l0));
            PK[32 + 2 * b + 1] = pack_bf16(phi_s(fmaf(-mean1, cs.x, acc[4 * b + 2]), rstd1, l1), phi_s(fmaf(-mean1, cs.y, acc[4 * b + 3]), rstd1, l1));
          }
          mbar_wait(bar_kvready, layer);
          float num[4][20];
          wgmma_fence();
#pragma unroll
          for (int hh = 0; hh < 4; hh++) {
            const uint32_t db = make_desc(sbase + OFF_STG + hh * 4096, 8192);
            wgmma_n40_rs<true>(num[hh], PK + 32 + 8 * hh, db);
            wgmma_n40_rs<false>(num[hh], PK + 32 + 8 * hh + 4, db + 128);
          }
          wgmma_commit();
          wgmma_wait<0>();
#pragma unroll
          for (int hh = 0; hh < 4; hh++) {
            const float* nm = num[hh];
            float r0 = rcpf(nm[16] + 1e-6f), r1 = rcpf(nm[18] + 1e-6f);
#pragma unroll
            for (int b = 0; b < 4; b++) {
              PK[8 * hh + 2 * b] = pack_bf16(nm[4 * b] * r0, nm[4 * b + 1] * r0);
              PK[8 * hh + 2 * b + 1] = pack_bf16(nm[4 * b + 2] * r1, nm[4 * b + 3] * r1);
            }
          }
        }
        };
        if (wide) run(IntC<1>{}); else run(IntC<0>{});
        TR(2 + 2 * T);
      }
      transpose_all(PK, c);
      __nv_bfloat16* p = prm.out + (size_t)row * D_ + 128 * j + 8 * c;
#pragma unroll
      for (int gi = 0; gi < 4; gi++) {
        *(uint4*)(p + 32 * gi) = make_uint4(PK[8 * gi], PK[8 * gi + 2], PK[8 * gi + 4], PK[8 * gi + 6]);
        *(uint4*)(p + 32 * gi + 8 * D_) = make_uint4(PK[8 * gi + 1], PK[8 * gi + 3], PK[8 * gi + 5], PK[8 * gi + 7]);
      }
      if (cta == 0 && threadIdx.x == 128) g_epoch = epoch;
    } else {
      uint32_t s = 0, ph = 0;
      float acc[4][4] = {};
#pragma unroll 1
      for (int lb = 0; lb < 80; lb++) {
        mbar_wait(full + 8 * (3 * cw + s), ph);
        const uint32_t da = make_desc(sbase + (3 * cw + s) * 32768, 8192);
#pragma unroll 1
        for (int k4 = 0; k4 < 16; k4 += 4) {
          wgmma_fence();
#pragma unroll
          for (int kk = 0; kk < 4; kk++) wgmma_n8_tn<false>(acc[kk], da + (k4 + kk) * 128, dones);
          wgmma_commit();
        }
        wgmma_wait<0>();
        if (w4 == 0 && lane == 0) mbar_arrive(empty + 8 * (3 * cw + s));
        if (++s == 3) { s = 0; ph ^= 1; }
        if ((lb & 3) == 3) {
          const int n = blockIdx.x + 4 * ((lb >> 2) * 2 + cw);
          int col = n < 48 ? ((n + 16) % 48) * 64 : 3072 + ((n & 4) ? F_ : 0) + (((n - 48) >> 3) * 4 + (n & 3)) * 64;
          if (c == 0) { g_cs[col + w4 * 16 + g] = (acc[0][0] + acc[1][0]) + (acc[2][0] + acc[3][0]); g_cs[col + w4 * 16 + g + 8] = (acc[0][2] + acc[1][2]) + (acc[2][2] + acc[3][2]); }
#pragma unroll
          for (int q = 0; q < 16; q++) acc[q >> 2][q & 3] = 0.f;
          if (lb == 23 || lb == 79) {
            wg_bar(1 + cw);
            if (w4 == 0 && lane == 0) { fence_gpu(); red_add_u32(&g_cscnt[lb > 23][0], 1); }
          }
        }
      }
    }
  } else {
    asm volatile("setmaxnreg.dec.sync.aligned.u32 40;");
    if (helper) {
      if (threadIdx.x == 0) {
        uint32_t s = 0, ph = 1;
#pragma unroll 1
        for (int q = 0; q < 160; q++) {
          const int lb = q >> 1, w = q & 1;
          const int n = blockIdx.x + 4 * ((lb >> 2) * 2 + w);
          const CUtensorMap* map = n < 48 ? &prm.hq : ((n & 4) ? &prm.hu : &prm.hg);
          int col = n < 48 ? ((n + 16) % 48) * 64 : (((n - 48) >> 3) * 4 + (n & 3)) * 64;
          const uint32_t sl = 3 * w + s;
          mbar_wait(empty + 8 * sl, ph);
          mbar_expect_tx(full + 8 * sl, 32768);
          tma_2d(sbase + sl * 32768, map, full + 8 * sl, col, (lb & 3) * 256);
          if (w && ++s == 3) { s = 0; ph ^= 1; }
        }
      }
    } else if (warp < 2) {
      uint32_t ready = 0, n = 0, dst = sbase;
      const bool lead = elect_one();
#pragma unroll 1
      for (int T = 0; T < 16; T++) {
        const int layer = T >> 3, tile = T & 7;
        const bool own = own_tile(T), wide = wide_tile(T);
        const uint32_t adv = (wide ? 3 : 2) * SLOT, dfill = wide ? 0x40000000u : 0x60000000u;
        uint32_t dtab = tile == 0 ? 0x44444455u : tile == 3 ? 0x44444344u : wide ? 0x44444444u : (tile == 1 || tile == 6) ? 0x66655544u : 0x66666666u;
        if (tile == 3) { dst += 2 * SLOT; if (dst >= sbase + NSLOT * SLOT) dst -= NSLOT * SLOT; }
        int col;
        const CUtensorMap* map = tile_info(prm, T, j, rank, col);
        const int kind = tile < 2 ? 3 : tile == 2 ? 0 : tile < 7 ? 1 : 2;
        const uint8_t* img = kind == 2 ? g_h + m * 56 * SLOT : (kind == 3 ? g_x2 : kind == 0 ? g_o : g_x1) + m * 16 * SLOT;
        const uint32_t* fl = &g_flag[layer][kind][m][lane];
        if ((0x8Du >> tile) & 1) ready = 0;
#pragma unroll 1
        for (int p = 0; p < (tile == 7 ? 28 : 8); p++) {
          const bool dummy = own && p == 0;
          int ab = p, kb, dk = 1;
          uint32_t need;
          if (tile == 7) {
            kb = p < 24 ? 7 * (p & 7) + 2 * (p >> 3) : 14 * p - 330; dk = p < 24 ? 1 : 7;
            need = p < 24 ? 1u << p : 3u << (2 * p - 24);
          } else {
            if (own) ab = p == 0 ? j : (p > j ? p : p - 1);
            kb = 2 * ab;
            need = (dummy || T < 2) ? 0u : 1u << ab;
            if (p == 7 && own && wide) need = 0xFFFF;
          }
          if (warp && (ready & need) != need) {
            uint32_t tries = 0;
            do {
              ready = __ballot_sync(~0u, ld_acquire(fl) == epoch);
              if (++tries > (1u << 20)) __trap();
            } while ((ready & need) != need);
            fence_async_global();
          }
          const CUtensorMap* mp_ = (dummy && T) ? map - 1 : map;
          const uint8_t* src = img + ab * 2 * SLOT;
#pragma unroll 1
          for (int e = 0; e < 2; e++) {
            const int X = n - (dtab & 15);
            dtab = (dtab >> 4) | dfill;
            const uint32_t fb = full + 8 * (n & 7);
            if (X >= 0) mbar_wait(empty + 8 * (X & 7), (X >> 3) & 1);
            if (lead) {
              if (warp == 0) {
                mbar_expect_tx(fb, adv - SLOT);
                tma_5d_mc(dst + SLOT + rank * 8192, mp_, fb, col, kb * 2);
                if (wide) tma_5d_mc(dst + 2 * SLOT + rank * 8192, mp_, fb, col + 64, kb * 2);
              } else if (dummy) {
                mbar_arrive(fb);
              } else {
                mbar_expect_tx(fb, SLOT);
                if (T < 2) tma_2d(dst, &prm.x, fb, kb * 64, m * 128);
                else bulk_load(dst, src, SLOT, fb);
              }
            }
            kb += dk; src += SLOT; n++;
            dst += adv; if (dst >= sbase + NSLOT * SLOT) dst -= NSLOT * SLOT;
          }
        }
      }
    } else {
      const int w = warp - 2;
      {
        float* z = &g_kv[(epoch & 1) ^ 1][0][0][0] + (size_t)cta * 528;
        for (int i = w * 32 + lane; i < 132; i += 64) *(float4*)(z + i * 4) = make_float4(0.f, 0.f, 0.f, 0.f);
      }
      int pf = 0;
      uint32_t sigph = 0;
#pragma unroll 1
      for (int ev = -1; ev < 18; ev++) {
        const int layer = ev >= 9, e = ev - 9 * layer;
        if (w == 0) {
          if (ev >= 0) {
            const bool se = e == 1 || e == 4;
            const uint32_t sb = se ? bar_sig2 : bar_sig, sp = se ? e >> 2 : sigph;
            mbar_wait(sb, sp); mbar_wait(sb + 8, sp);
            if (!se) sigph ^= 1;
            const int kind = (0x222211033ull >> (4 * e)) & 3, sub = (0x321010010ull >> (4 * e)) & 3;
            if (lane == 0) { fence_gpu(); st_relaxed(&g_flag[layer][kind][m][sub * 8 + j], epoch); }
          }
          const int hi = min(16, layer * 8 + (int)((0x9886544311ull >> (4 * (e + 1))) & 15));
#pragma unroll 1
          for (; pf < hi; pf++) {
            int col;
            const CUtensorMap* map = tile_info(prm, pf, j, rank, col);
            const int kb = mp + 8 * (lane >> 1);
            if (kb < ((pf & 7) == 7 ? 56 : 16) && (!(lane & 1) || wide_tile(pf))) tma_5d_prefetch(map, col + 64 * (lane & 1), kb * 2);
          }
          __syncwarp();
        } else if (e == -1 || e == 2) {
          poll_eq(&g_cscnt[e > 0][0], epoch * 8);
          fence_async_global();
          const uint32_t cb = e > 0 ? bar_csgu : bar_csq;
          if (lane == 0) mbar_expect_tx(cb, e > 0 ? 3584 : 1536);
          __syncwarp();
          if (lane < (e > 0 ? 14 : 6)) {
            const int col = e > 0 ? 3072 + (lane & 1) * F_ + 448 * j + (lane >> 1) * 64
                                  : lane < 4 ? 1024 + (lane & 1) * 1024 + 128 * j + (lane >> 1) * 64 : 128 * j + (lane - 4) * 64;
            bulk_load(sbase + (e > 0 ? OFF_CSGU : OFF_CSQ) + lane * 256, &g_cs[col], 256, cb);
          }
          __syncwarp();
        }
        if (e == 1) {
          mbar_wait(bar_kvdone, layer);
          if (w == 0 && lane == 0) { fence_gpu(); red_add_u32(&g_kvcnt[layer][j][0], 1); }
          poll_eq(&g_kvcnt[layer][j][0], epoch * 16);
          const float* kvp = &g_kv[epoch & 1][layer][4 * j + 2 * w][0];
#pragma unroll 1
          for (int it = 0; it < 4; it++) {
            const float* src = kvp + (it >> 1) * 1056;
            float4 v[4];
#pragma unroll
            for (int q = 0; q < 4; q++) v[q] = __ldcg((const float4*)(src + (it & 1) * 512 + (q * 32 + lane) * 4));
            float zz = __ldcg(src + 1024 + lane);
            const uint32_t hb = sbase + OFF_STG + (2 * w + (it >> 1)) * 4096;
#pragma unroll
            for (int q = 0; q < 4; q++) {
              const int d = (it & 1) * 16 + q * 4 + (lane >> 3), jb = (lane & 1) * 2;
              const uint32_t rb = hb + d * 128 + ((lane >> 1) & 3) * 4;
              sts_u32(rb + ((jb ^ (d & 7)) << 4), pack_bf16(v[q].x, v[q].y));
              sts_u32(rb + (((jb + 1) ^ (d & 7)) << 4), pack_bf16(v[q].z, v[q].w));
            }
            const uint32_t zp = pack_bf16(zz, zz);
            sts_v4(hb + lane * 128 + ((4 ^ (lane & 7)) << 4), make_uint4(zp, zp, zp, zp));
          }
          fence_async_smem();
          __syncwarp();
          if (lane == 0) mbar_arrive(bar_kvready);
        }
      }
    }
  }
  __syncwarp();
  cluster_sync();
}

typedef CUresult (*EncodeTiledFn)(CUtensorMap*, CUtensorMapDataType, cuuint32_t, void*, const cuuint64_t*, const cuuint64_t*, const cuuint32_t*, const cuuint32_t*,
                                  CUtensorMapInterleave, CUtensorMapSwizzle, CUtensorMapL2promotion, CUtensorMapFloatOOBfill);

void make_wmap(EncodeTiledFn enc, CUtensorMap* m, const void* ptr, uint64_t rows, uint64_t cols, bool perm) {
  uint64_t rs = cols * 2;
  cuuint64_t gd[5] = {cols, 2, 4, 4, rows / 32};
  cuuint64_t gs[4] = {rs, (perm ? 8 : 2) * rs, (perm ? 2 : 8) * rs, 32 * rs};
  cuuint32_t bd[5] = {64, 2, 4, 4, 2}, es[5] = {1, 1, 1, 1, 1};
  enc(m, CU_TENSOR_MAP_DATA_TYPE_BFLOAT16, 5, (void*)ptr, gd, gs, bd, es, CU_TENSOR_MAP_INTERLEAVE_NONE, CU_TENSOR_MAP_SWIZZLE_128B,
      CU_TENSOR_MAP_L2_PROMOTION_L2_256B, CU_TENSOR_MAP_FLOAT_OOB_FILL_NONE);
}

void make_2d(EncodeTiledFn enc, CUtensorMap* m, const void* ptr, uint64_t rows, uint64_t cols, uint32_t box_rows) {
  cuuint64_t gd[2] = {cols, rows}, gs[1] = {cols * 2}; cuuint32_t bd[2] = {64, box_rows}, es[2] = {1, 1};
  enc(m, CU_TENSOR_MAP_DATA_TYPE_BFLOAT16, 2, (void*)ptr, gd, gs, bd, es, CU_TENSOR_MAP_INTERLEAVE_NONE, CU_TENSOR_MAP_SWIZZLE_128B,
      CU_TENSOR_MAP_L2_PROMOTION_L2_256B, CU_TENSOR_MAP_FLOAT_OOB_FILL_NONE);
}

}

extern "C" void kernel_launch(void* const* d_in, const int* in_sizes, int n_in, void* d_out, int out_size) {
  const __nv_bfloat16* x = (const __nv_bfloat16*)d_in[0];
  const __nv_bfloat16* wqkv = (const __nv_bfloat16*)d_in[1];
  const __nv_bfloat16* wo = (const __nv_bfloat16*)d_in[2];
  const __nv_bfloat16* wg = (const __nv_bfloat16*)d_in[4];
  const __nv_bfloat16* wu = (const __nv_bfloat16*)d_in[5];
  const __nv_bfloat16* wd = (const __nv_bfloat16*)d_in[6];

  void* fn = nullptr; cudaDriverEntryPointQueryResult qr;
  cudaGetDriverEntryPoint("cuTensorMapEncodeTiled", &fn, cudaEnableDefault, &qr);
  EncodeTiledFn enc = (EncodeTiledFn)fn;
  Params prm;
  make_2d(enc, &prm.x, x, S_, D_, 128);
  make_wmap(enc, &prm.wqkv_n, wqkv, D_, 3 * D_, false);
  make_wmap(enc, &prm.wqkv_p, wqkv, D_, 3 * D_, true);
  make_wmap(enc, &prm.wo_n, wo, D_, D_, false);
  make_wmap(enc, &prm.wo_p, wo, D_, D_, true);
  make_wmap(enc, &prm.wg_n, wg, D_, F_, false);
  make_wmap(enc, &prm.wu_n, wu, D_, F_, false);
  make_2d(enc, &prm.hq, wqkv, D_, 3 * D_, 256);
  make_2d(enc, &prm.hg, wg, D_, F_, 256);
  make_2d(enc, &prm.hu, wu, D_, F_, 256);
  make_wmap(enc, &prm.wg_p, wg, D_, F_, true);
  make_wmap(enc, &prm.wu_p, wu, D_, F_, true);
  make_wmap(enc, &prm.wd_p, wd, F_, D_, true);
  prm.xin = x; prm.out = (__nv_bfloat16*)d_out;

  cudaFuncSetAttribute(fused_kernel, cudaFuncAttributeMaxDynamicSharedMemorySize, SMEM_BYTES);
  cudaLaunchConfig_t cfg = {};
  cfg.gridDim = dim3(132); cfg.blockDim = dim3(384); cfg.dynamicSmemBytes = SMEM_BYTES; cfg.stream = cudaStreamPerThread;
  cudaLaunchAttribute at[1];
  at[0].id = cudaLaunchAttributeClusterDimension; at[0].val.clusterDim.x = 2; at[0].val.clusterDim.y = 1; at[0].val.clusterDim.z = 1;
  cfg.attrs = at; cfg.numAttrs = 1;
  cudaLaunchKernelEx(&cfg, fused_kernel, prm);
}
```

```cpp
#include <cuda_runtime.h>
#include <cuda_bf16.h>
#include <cuda.h>
#include <stdint.h>

namespace {

constexpr int S_ = 2048, D_ = 1024, F_ = 3584;
constexpr int NSLOT = 12;
constexpr uint32_t SLOT = 16384;
constexpr uint32_t OFF_STG = NSLOT * SLOT;
constexpr uint32_t OFF_CSQ = OFF_STG + 32768;
constexpr uint32_t OFF_ONES = OFF_CSQ + 1536;
constexpr uint32_t OFF_BAR = OFF_ONES + 256;
constexpr uint32_t SMEM_BYTES = OFF_BAR + 512;
constexpr uint32_t OFF_CSGU = OFF_STG + 24576;

__device__ __align__(1024) uint8_t g_o[16 * 16 * SLOT];
__device__ __align__(1024) uint8_t g_x1[16 * 16 * SLOT];
__device__ __align__(1024) uint8_t g_x2[16 * 16 * SLOT];
__device__ __align__(1024) uint8_t g_h[16 * 56 * SLOT];
__device__ __align__(128) float2 g_stats[4][S_][8];
__device__ __align__(128) float g_cs[2][3072 + 2 * F_];
__device__ __align__(128) float g_kv[2][2][8][4224];
__device__ __align__(128) uint32_t g_flag[2][4][16][32];
__device__ __align__(128) uint32_t g_kvcnt[2][8][32];
__device__ __align__(128) uint32_t g_cscnt[11][32];
__device__ uint32_t g_epoch;

struct Params {
  CUtensorMap x, wqkv_n, wqkv_p, wo_p, wg_p, wu_p, wd_p;
  const __nv_bfloat16* xin;
  __nv_bfloat16* out;
};

__device__ __forceinline__ uint32_t smem_u32(const void* p) { return (uint32_t)__cvta_generic_to_shared(p); }
__device__ __forceinline__ void mbar_init(uint32_t bar, uint32_t count) { asm volatile("mbarrier.init.shared::cta.b64 [%0], %1;" :: "r"(bar), "r"(count) : "memory"); }
__device__ __forceinline__ void mbar_expect_tx(uint32_t bar, uint32_t bytes) { asm volatile("mbarrier.arrive.expect_tx.shared::cta.b64 _, [%0], %1;" :: "r"(bar), "r"(bytes) : "memory"); }
__device__ __forceinline__ void mbar_arrive(uint32_t bar) { asm volatile("mbarrier.arrive.shared::cta.b64 _, [%0];" :: "r"(bar) : "memory"); }
__device__ __forceinline__ void mbar_arrive_cluster(uint32_t bar, uint32_t cta) {
  asm volatile("{\n.reg .b32 ra;\nmapa.shared::cluster.u32 ra, %0, %1;\nmbarrier.arrive.shared::cluster.b64 _, [ra];\n}\n" :: "r"(bar), "r"(cta) : "memory");
}
__device__ __forceinline__ void mbar_arrive_if(uint32_t bar, bool pred) {
  asm volatile("{\n.reg .pred p;\nsetp.ne.b32 p, %1, 0;\n@p mbarrier.arrive.shared::cta.b64 _, [%0];\n}\n" :: "r"(bar), "r"((uint32_t)pred) : "memory");
}
__device__ __forceinline__ void mbar_arrive_remote_if(uint32_t cluster_addr, bool pred) {
  asm volatile("{\n.reg .pred p;\nsetp.ne.b32 p, %1, 0;\n@p mbarrier.arrive.shared::cluster.b64 _, [%0];\n}\n" :: "r"(cluster_addr), "r"((uint32_t)pred) : "memory");
}
__device__ __forceinline__ uint32_t mapa(uint32_t addr, uint32_t cta) { uint32_t r; asm("mapa.shared::cluster.u32 %0, %1, %2;" : "=r"(r) : "r"(addr), "r"(cta)); return r; }
__device__ __forceinline__ void st_f2_if(float2* ptr, float a, float b, bool pred) {
  asm volatile("{\n.reg .pred p;\nsetp.ne.b32 p, %3, 0;\n@p st.global.v2.f32 [%0], {%1, %2};\n}\n" :: "l"(ptr), "f"(a), "f"(b), "r"((uint32_t)pred) : "memory");
}
__device__ __forceinline__ void red_add_f32_if(float* ptr, float v, bool pred) {
  asm volatile("{\n.reg .pred p;\nsetp.ne.b32 p, %2, 0;\n@p red.relaxed.gpu.global.add.f32 [%0], %1;\n}\n" :: "l"(ptr), "f"(v), "r"((uint32_t)pred) : "memory");
}
__device__ __forceinline__ void mbar_wait(uint32_t bar, uint32_t parity) {
  asm volatile("{\n.reg .pred p;\n.reg .b32 n;\nmov.b32 n, 0;\nWAIT_LOOP:\n"
               "mbarrier.try_wait.parity.shared::cta.b64 p, [%0], %1;\n@p bra WAIT_DONE;\n"
               "add.u32 n, n, 1;\nsetp.lt.u32 p, n, 1048576;\n@p bra WAIT_LOOP;\ntrap;\nWAIT_DONE:\n}\n" :: "r"(bar), "r"(parity) : "memory");
}
__device__ __forceinline__ uint32_t ld_acquire(const uint32_t* p) { uint32_t v; asm volatile("ld.acquire.gpu.global.u32 %0, [%1];" : "=r"(v) : "l"(p) : "memory"); return v; }
__device__ __forceinline__ void poll_eq(const uint32_t* p, uint32_t want) {
  uint32_t n = 0;
  while (ld_acquire(p) != want) { if (++n > (1u << 20)) __trap(); }
}
__device__ __forceinline__ void tma_2d(uint32_t dst, const CUtensorMap* m, uint32_t bar, int c0, int c1) {
  asm volatile("cp.async.bulk.tensor.2d.shared::cluster.global.mbarrier::complete_tx::bytes [%0], [%1, {%3, %4}], [%2];"
    :: "r"(dst), "l"((uint64_t)m), "r"(bar), "r"(c0), "r"(c1) : "memory");
}
__device__ __forceinline__ void tma_5d_mc(uint32_t dst, const CUtensorMap* m, uint32_t bar, int c0, int c4) {
  asm volatile("cp.async.bulk.tensor.5d.shared::cluster.global.mbarrier::complete_tx::bytes.multicast::cluster [%0], [%1, {%3, %5, %5, %5, %4}], [%2], %6;"
    :: "r"(dst), "l"((uint64_t)m), "r"(bar), "r"(c0), "r"(c4), "r"(0), "h"((uint16_t)3) : "memory");
}
__device__ __forceinline__ void tma_5d(uint32_t dst, const CUtensorMap* m, uint32_t bar, int c0, int c4) {
  asm volatile("cp.async.bulk.tensor.5d.shared::cluster.global.mbarrier::complete_tx::bytes [%0], [%1, {%3, %5, %5, %5, %4}], [%2];"
    :: "r"(dst), "l"((uint64_t)m), "r"(bar), "r"(c0), "r"(c4), "r"(0) : "memory");
}
__device__ __forceinline__ void tma_5d_prefetch(const CUtensorMap* m, int c0, int c4) {
  asm volatile("cp.async.bulk.prefetch.tensor.5d.L2.global.tile [%0, {%1, %3, %3, %3, %2}];" :: "l"((uint64_t)m), "r"(c0), "r"(c4), "r"(0) : "memory");
}
__device__ __forceinline__ void bulk_load(uint32_t dst, const void* src, uint32_t bytes, uint32_t bar) {
  asm volatile("cp.async.bulk.shared::cluster.global.mbarrier::complete_tx::bytes [%0], [%1], %2, [%3];"
    :: "r"(dst), "l"((uint64_t)src), "r"(bytes), "r"(bar) : "memory");
}
__device__ __forceinline__ void bulk_store(void* dst, uint32_t src, uint32_t bytes) {
  asm volatile("cp.async.bulk.global.shared::cta.bulk_group [%0], [%1], %2;" :: "l"((uint64_t)dst), "r"(src), "r"(bytes) : "memory");
}
#define PFTAB 0x988654431ull
#define OWN_FENCE
__device__ __forceinline__ void bulk_reduce_f32(void* dst, uint32_t src, uint32_t bytes) {
  asm volatile("cp.reduce.async.bulk.global.shared::cta.bulk_group.add.f32 [%0], [%1], %2;" :: "l"((uint64_t)dst), "r"(src), "r"(bytes) : "memory");
}
__device__ __forceinline__ void wgmma_fence() { asm volatile("wgmma.fence.sync.aligned;" ::: "memory"); }
__device__ __forceinline__ void wgmma_commit() { asm volatile("wgmma.commit_group.sync.aligned;" ::: "memory"); }
template<int N> __device__ __forceinline__ void wgmma_wait() { asm volatile("wgmma.wait_group.sync.aligned %0;" :: "n"(N) : "memory"); }
__device__ __forceinline__ void cluster_sync() { asm volatile("barrier.cluster.arrive.release.aligned;\nbarrier.cluster.wait.acquire.aligned;" ::: "memory"); }
__device__ __forceinline__ void cluster_wait() { asm volatile("barrier.cluster.wait.acquire.aligned;" ::: "memory"); }
__device__ __forceinline__ void fence_async_smem() { asm volatile("fence.proxy.async.shared::cta;" ::: "memory"); }
__device__ __forceinline__ void fence_async_global() { asm volatile("fence.proxy.async.global;" ::: "memory"); }
__device__ __forceinline__ void fence_gpu() { asm volatile("fence.acq_rel.gpu;" ::: "memory"); }
__device__ __forceinline__ void wg_bar(int id) { asm volatile("bar.sync %0, 128;" :: "r"(id) : "memory"); }
__device__ __forceinline__ void st_relaxed(uint32_t* p, uint32_t v) { asm volatile("st.relaxed.gpu.global.u32 [%0], %1;" :: "l"(p), "r"(v) : "memory"); }
__device__ __forceinline__ void red_add_u32(uint32_t* p, uint32_t v) { asm volatile("red.relaxed.gpu.global.add.u32 [%0], %1;" :: "l"(p), "r"(v) : "memory"); }
__device__ __forceinline__ void red_add_f32(float* p, float v) { asm volatile("red.relaxed.gpu.global.add.f32 [%0], %1;" :: "l"(p), "f"(v) : "memory"); }
__device__ __forceinline__ void red_add_v4(float* p, float a, float b, float c, float d) {
  asm volatile("red.relaxed.gpu.global.add.v4.f32 [%0], {%1, %2, %3, %4};" :: "l"(p), "f"(a), "f"(b), "f"(c), "f"(d) : "memory");
}
__device__ __forceinline__ void stmatrix_x4(uint32_t addr, uint32_t r0, uint32_t r1, uint32_t r2, uint32_t r3) {
  asm volatile("stmatrix.sync.aligned.m8n8.x4.shared.b16 [%0], {%1, %2, %3, %4};" :: "r"(addr), "r"(r0), "r"(r1), "r"(r2), "r"(r3) : "memory");
}
__device__ __forceinline__ float2 lds_f2(uint32_t addr) { float2 v; asm volatile("ld.shared.v2.f32 {%0, %1}, [%2];" : "=f"(v.x), "=f"(v.y) : "r"(addr)); return v; }
__device__ __forceinline__ void sts_u32(uint32_t addr, uint32_t v) { asm volatile("st.shared.u32 [%0], %1;" :: "r"(addr), "r"(v) : "memory"); }
__device__ __forceinline__ void sts_v4(uint32_t addr, uint4 v) { asm volatile("st.shared.v4.u32 [%0], {%1, %2, %3, %4};" :: "r"(addr), "r"(v.x), "r"(v.y), "r"(v.z), "r"(v.w) : "memory"); }
__device__ __forceinline__ uint32_t pack_bf16(float lo, float hi) { uint32_t r; asm("cvt.rn.bf16x2.f32 %0, %1, %2;" : "=r"(r) : "f"(hi), "f"(lo)); return r; }
__device__ __forceinline__ float bf_lo(uint32_t v) { return __uint_as_float(v << 16); }
__device__ __forceinline__ float bf_hi(uint32_t v) { return __uint_as_float(v & 0xffff0000u); }
__device__ __forceinline__ float ex2f(float x) { float r; asm("ex2.approx.ftz.f32 %0, %1;" : "=f"(r) : "f"(x)); return r; }
__device__ __forceinline__ float rcpf(float x) { float r; asm("rcp.approx.ftz.f32 %0, %1;" : "=f"(r) : "f"(x)); return r; }
__device__ __forceinline__ float phif(float t) { return (t > 0.f ? t + 1.f : ex2f(t * 1.4426950408889634f)) + 1e-6f; }
__device__ __forceinline__ uint32_t make_desc(uint32_t addr, uint32_t lbo) { return ((addr & 0x3FFFF) >> 4) | ((lbo >> 4) << 16); }
__device__ __forceinline__ bool mbar_test(uint32_t bar, uint32_t parity) {
  uint32_t ok;
  asm volatile("{\n.reg .pred p;\nmbarrier.test_wait.parity.shared::cta.b64 p, [%1], %2;\nselp.u32 %0, 1, 0, p;\n}\n" : "=r"(ok) : "r"(bar), "r"(parity) : "memory");
  return ok;
}
__device__ __forceinline__ int lane_id() { int r; asm volatile("mov.u32 %0, %%laneid;" : "=r"(r)); return r; }
__device__ __forceinline__ uint32_t load_epoch() { return __ldcg(&g_epoch) + 1; }
__device__ __forceinline__ bool elect_one() {
  uint32_t r;
  asm volatile("{\n.reg .pred p;\nelect.sync _|p, 0xffffffff;\nselp.u32 %0, 1, 0, p;\n}\n" : "=r"(r));
  return r;
}
__device__ __forceinline__ uint32_t hmul2(uint32_t a, uint32_t b) { uint32_t r; asm("mul.rn.bf16x2 %0, %1, %2;" : "=r"(r) : "r"(a), "r"(b)); return r; }
__device__ __forceinline__ unsigned long long gtime() { unsigned long long t; asm volatile("mov.u64 %0, %%globaltimer;" : "=l"(t)); return t; }

template<bool INIT> __device__ __forceinline__ void wgmma_n256_ss(float* d, uint32_t da, uint32_t db) {
  if constexpr (INIT) {
  asm volatile("{\n.reg .pred p;\n.reg .b64 da, db;\nsetp.ne.b32 p, 0, 0;\nmov.b64 da, {%128, 0x40000040};\nmov.b64 db, {%129, 0x40000040};\nwgmma.mma_async.sync.aligned.m64n256k16.f32.bf16.bf16 {%0, %1, %2, %3, %4, %5, %6, %7, %8, %9, %10, %11, %12, %13, %14, %15, %16, %17, %18, %19, %20, %21, %22, %23, %24, %25, %26, %27, %28, %29, %30, %31, %32, %33, %34, %35, %36, %37, %38, %39, %40, %41, %42, %43, %44, %45, %46, %47, %48, %49, %50, %51, %52, %53, %54, %55, %56, %57, %58, %59, %60, %61, %62, %63, %64, %65, %66, %67, %68, %69, %70, %71, %72, %73, %74, %75, %76, %77, %78, %79, %80, %81, %82, %83, %84, %85, %86, %87, %88, %89, %90, %91, %92, %93, %94, %95, %96, %97, %98, %99, %100, %101, %102, %103, %104, %105, %106, %107, %108, %109, %110, %111, %112, %113, %114, %115, %116, %117, %118, %119, %120, %121, %122, %123, %124, %125, %126, %127}, da, db, p, 1, 1, 0, 1;\n}\n"
    : "=f"(d[0]), "=f"(d[1]), "=f"(d[2]), "=f"(d[3]), "=f"(d[4]), "=f"(d[5]), "=f"(d[6]), "=f"(d[7]), "=f"(d[8]), "=f"(d[9]), "=f"(d[10]), "=f"(d[11]), "=f"(d[12]), "=f"(d[13]), "=f"(d[14]), "=f"(d[15]), "=f"(d[16]), "=f"(d[17]), "=f"(d[18]), "=f"(d[19]), "=f"(d[20]), "=f"(d[21]), "=f"(d[22]), "=f"(d[23]), "=f"(d[24]), "=f"(d[25]), "=f"(d[26]), "=f"(d[27]), "=f"(d[28]), "=f"(d[29]), "=f"(d[30]), "=f"(d[31]), "=f"(d[32]), "=f"(d[33]), "=f"(d[34]), "=f"(d[35]), "=f"(d[36]), "=f"(d[37]), "=f"(d[38]), "=f"(d[39]), "=f"(d[40]), "=f"(d[41]), "=f"(d[42]), "=f"(d[43]), "=f"(d[44]), "=f"(d[45]), "=f"(d[46]), "=f"(d[47]), "=f"(d[48]), "=f"(d[49]), "=f"(d[50]), "=f"(d[51]), "=f"(d[52]), "=f"(d[53]), "=f"(d[54]), "=f"(d[55]), "=f"(d[56]), "=f"(d[57]), "=f"(d[58]), "=f"(d[59]), "=f"(d[60]), "=f"(d[61]), "=f"(d[62]), "=f"(d[63]), "=f"(d[64]), "=f"(d[65]), "=f"(d[66]), "=f"(d[67]), "=f"(d[68]), "=f"(d[69]), "=f"(d[70]), "=f"(d[71]), "=f"(d[72]), "=f"(d[73]), "=f"(d[74]), "=f"(d[75]), "=f"(d[76]), "=f"(d[77]), "=f"(d[78]), "=f"(d[79]), "=f"(d[80]), "=f"(d[81]), "=f"(d[82]), "=f"(d[83]), "=f"(d[84]), "=f"(d[85]), "=f"(d[86]), "=f"(d[87]), "=f"(d[88]), "=f"(d[89]), "=f"(d[90]), "=f"(d[91]), "=f"(d[92]), "=f"(d[93]), "=f"(d[94]), "=f"(d[95]), "=f"(d[96]), "=f"(d[97]), "=f"(d[98]), "=f"(d[99]), "=f"(d[100]), "=f"(d[101]), "=f"(d[102]), "=f"(d[103]), "=f"(d[104]), "=f"(d[105]), "=f"(d[106]), "=f"(d[107]), "=f"(d[108]), "=f"(d[109]), "=f"(d[110]), "=f"(d[111]), "=f"(d[112]), "=f"(d[113]), "=f"(d[114]), "=f"(d[115]), "=f"(d[116]), "=f"(d[117]), "=f"(d[118]), "=f"(d[119]), "=f"(d[120]), "=f"(d[121]), "=f"(d[122]), "=f"(d[123]), "=f"(d[124]), "=f"(d[125]), "=f"(d[126]), "=f"(d[127])
    : "r"(da), "r"(db));
  } else {
  asm volatile("{\n.reg .pred p;\n.reg .b64 da, db;\nsetp.ne.b32 p, 1, 0;\nmov.b64 da, {%128, 0x40000040};\nmov.b64 db, {%129, 0x40000040};\nwgmma.mma_async.sync.aligned.m64n256k16.f32.bf16.bf16 {%0, %1, %2, %3, %4, %5, %6, %7, %8, %9, %10, %11, %12, %13, %14, %15, %16, %17, %18, %19, %20, %21, %22, %23, %24, %25, %26, %27, %28, %29, %30, %31, %32, %33, %34, %35, %36, %37, %38, %39, %40, %41, %42, %43, %44, %45, %46, %47, %48, %49, %50, %51, %52, %53, %54, %55, %56, %57, %58, %59, %60, %61, %62, %63, %64, %65, %66, %67, %68, %69, %70, %71, %72, %73, %74, %75, %76, %77, %78, %79, %80, %81, %82, %83, %84, %85, %86, %87, %88, %89, %90, %91, %92, %93, %94, %95, %96, %97, %98, %99, %100, %101, %102, %103, %104, %105, %106, %107, %108, %109, %110, %111, %112, %113, %114, %115, %116, %117, %118, %119, %120, %121, %122, %123, %124, %125, %126, %127}, da, db, p, 1, 1, 0, 1;\n}\n"
    : "+f"(d[0]), "+f"(d[1]), "+f"(d[2]), "+f"(d[3]), "+f"(d[4]), "+f"(d[5]), "+f"(d[6]), "+f"(d[7]), "+f"(d[8]), "+f"(d[9]), "+f"(d[10]), "+f"(d[11]), "+f"(d[12]), "+f"(d[13]), "+f"(d[14]), "+f"(d[15]), "+f"(d[16]), "+f"(d[17]), "+f"(d[18]), "+f"(d[19]), "+f"(d[20]), "+f"(d[21]), "+f"(d[22]), "+f"(d[23]), "+f"(d[24]), "+f"(d[25]), "+f"(d[26]), "+f"(d[27]), "+f"(d[28]), "+f"(d[29]), "+f"(d[30]), "+f"(d[31]), "+f"(d[32]), "+f"(d[33]), "+f"(d[34]), "+f"(d[35]), "+f"(d[36]), "+f"(d[37]), "+f"(d[38]), "+f"(d[39]), "+f"(d[40]), "+f"(d[41]), "+f"(d[42]), "+f"(d[43]), "+f"(d[44]), "+f"(d[45]), "+f"(d[46]), "+f"(d[47]), "+f"(d[48]), "+f"(d[49]), "+f"(d[50]), "+f"(d[51]), "+f"(d[52]), "+f"(d[53]), "+f"(d[54]), "+f"(d[55]), "+f"(d[56]), "+f"(d[57]), "+f"(d[58]), "+f"(d[59]), "+f"(d[60]), "+f"(d[61]), "+f"(d[62]), "+f"(d[63]), "+f"(d[64]), "+f"(d[65]), "+f"(d[66]), "+f"(d[67]), "+f"(d[68]), "+f"(d[69]), "+f"(d[70]), "+f"(d[71]), "+f"(d[72]), "+f"(d[73]), "+f"(d[74]), "+f"(d[75]), "+f"(d[76]), "+f"(d[77]), "+f"(d[78]), "+f"(d[79]), "+f"(d[80]), "+f"(d[81]), "+f"(d[82]), "+f"(d[83]), "+f"(d[84]), "+f"(d[85]), "+f"(d[86]), "+f"(d[87]), "+f"(d[88]), "+f"(d[89]), "+f"(d[90]), "+f"(d[91]), "+f"(d[92]), "+f"(d[93]), "+f"(d[94]), "+f"(d[95]), "+f"(d[96]), "+f"(d[97]), "+f"(d[98]), "+f"(d[99]), "+f"(d[100]), "+f"(d[101]), "+f"(d[102]), "+f"(d[103]), "+f"(d[104]), "+f"(d[105]), "+f"(d[106]), "+f"(d[107]), "+f"(d[108]), "+f"(d[109]), "+f"(d[110]), "+f"(d[111]), "+f"(d[112]), "+f"(d[113]), "+f"(d[114]), "+f"(d[115]), "+f"(d[116]), "+f"(d[117]), "+f"(d[118]), "+f"(d[119]), "+f"(d[120]), "+f"(d[121]), "+f"(d[122]), "+f"(d[123]), "+f"(d[124]), "+f"(d[125]), "+f"(d[126]), "+f"(d[127])
    : "r"(da), "r"(db));
  }
}
template<bool INIT> __device__ __forceinline__ void wgmma_n128_ss(float* d, uint32_t da, uint32_t db) {
  if constexpr (INIT) {
  asm volatile("{\n.reg .pred p;\n.reg .b64 da, db;\nsetp.ne.b32 p, 0, 0;\nmov.b64 da, {%64, 0x40000040};\nmov.b64 db, {%65, 0x40000040};\nwgmma.mma_async.sync.aligned.m64n128k16.f32.bf16.bf16 {%0, %1, %2, %3, %4, %5, %6, %7, %8, %9, %10, %11, %12, %13, %14, %15, %16, %17, %18, %19, %20, %21, %22, %23, %24, %25, %26, %27, %28, %29, %30, %31, %32, %33, %34, %35, %36, %37, %38, %39, %40, %41, %42, %43, %44, %45, %46, %47, %48, %49, %50, %51, %52, %53, %54, %55, %56, %57, %58, %59, %60, %61, %62, %63}, da, db, p, 1, 1, 0, 1;\n}\n"
    : "=f"(d[0]), "=f"(d[1]), "=f"(d[2]), "=f"(d[3]), "=f"(d[4]), "=f"(d[5]), "=f"(d[6]), "=f"(d[7]), "=f"(d[8]), "=f"(d[9]), "=f"(d[10]), "=f"(d[11]), "=f"(d[12]), "=f"(d[13]), "=f"(d[14]), "=f"(d[15]), "=f"(d[16]), "=f"(d[17]), "=f"(d[18]), "=f"(d[19]), "=f"(d[20]), "=f"(d[21]), "=f"(d[22]), "=f"(d[23]), "=f"(d[24]), "=f"(d[25]), "=f"(d[26]), "=f"(d[27]), "=f"(d[28]), "=f"(d[29]), "=f"(d[30]), "=f"(d[31]), "=f"(d[32]), "=f"(d[33]), "=f"(d[34]), "=f"(d[35]), "=f"(d[36]), "=f"(d[37]), "=f"(d[38]), "=f"(d[39]), "=f"(d[40]), "=f"(d[41]), "=f"(d[42]), "=f"(d[43]), "=f"(d[44]), "=f"(d[45]), "=f"(d[46]), "=f"(d[47]), "=f"(d[48]), "=f"(d[49]), "=f"(d[50]), "=f"(d[51]), "=f"(d[52]), "=f"(d[53]), "=f"(d[54]), "=f"(d[55]), "=f"(d[56]), "=f"(d[57]), "=f"(d[58]), "=f"(d[59]), "=f"(d[60]), "=f"(d[61]), "=f"(d[62]), "=f"(d[63])
    : "r"(da), "r"(db));
  } else {
  asm volatile("{\n.reg .pred p;\n.reg .b64 da, db;\nsetp.ne.b32 p, 1, 0;\nmov.b64 da, {%64, 0x40000040};\nmov.b64 db, {%65, 0x40000040};\nwgmma.mma_async.sync.aligned.m64n128k16.f32.bf16.bf16 {%0, %1, %2, %3, %4, %5, %6, %7, %8, %9, %10, %11, %12, %13, %14, %15, %16, %17, %18, %19, %20, %21, %22, %23, %24, %25, %26, %27, %28, %29, %30, %31, %32, %33, %34, %35, %36, %37, %38, %39, %40, %41, %42, %43, %44, %45, %46, %47, %48, %49, %50, %51, %52, %53, %54, %55, %56, %57, %58, %59, %60, %61, %62, %63}, da, db, p, 1, 1, 0, 1;\n}\n"
    : "+f"(d[0]), "+f"(d[1]), "+f"(d[2]), "+f"(d[3]), "+f"(d[4]), "+f"(d[5]), "+f"(d[6]), "+f"(d[7]), "+f"(d[8]), "+f"(d[9]), "+f"(d[10]), "+f"(d[11]), "+f"(d[12]), "+f"(d[13]), "+f"(d[14]), "+f"(d[15]), "+f"(d[16]), "+f"(d[17]), "+f"(d[18]), "+f"(d[19]), "+f"(d[20]), "+f"(d[21]), "+f"(d[22]), "+f"(d[23]), "+f"(d[24]), "+f"(d[25]), "+f"(d[26]), "+f"(d[27]), "+f"(d[28]), "+f"(d[29]), "+f"(d[30]), "+f"(d[31]), "+f"(d[32]), "+f"(d[33]), "+f"(d[34]), "+f"(d[35]), "+f"(d[36]), "+f"(d[37]), "+f"(d[38]), "+f"(d[39]), "+f"(d[40]), "+f"(d[41]), "+f"(d[42]), "+f"(d[43]), "+f"(d[44]), "+f"(d[45]), "+f"(d[46]), "+f"(d[47]), "+f"(d[48]), "+f"(d[49]), "+f"(d[50]), "+f"(d[51]), "+f"(d[52]), "+f"(d[53]), "+f"(d[54]), "+f"(d[55]), "+f"(d[56]), "+f"(d[57]), "+f"(d[58]), "+f"(d[59]), "+f"(d[60]), "+f"(d[61]), "+f"(d[62]), "+f"(d[63])
    : "r"(da), "r"(db));
  }
}
template<bool INIT> __device__ __forceinline__ void wgmma_n256_rs(float* d, const uint32_t* a, uint32_t db) {
  if constexpr (INIT) {
  asm volatile("{\n.reg .pred p;\n.reg .b64 db;\nsetp.ne.b32 p, 0, 0;\nmov.b64 db, {%132, 0x40000040};\nwgmma.mma_async.sync.aligned.m64n256k16.f32.bf16.bf16 {%0, %1, %2, %3, %4, %5, %6, %7, %8, %9, %10, %11, %12, %13, %14, %15, %16, %17, %18, %19, %20, %21, %22, %23, %24, %25, %26, %27, %28, %29, %30, %31, %32, %33, %34, %35, %36, %37, %38, %39, %40, %41, %42, %43, %44, %45, %46, %47, %48, %49, %50, %51, %52, %53, %54, %55, %56, %57, %58, %59, %60, %61, %62, %63, %64, %65, %66, %67, %68, %69, %70, %71, %72, %73, %74, %75, %76, %77, %78, %79, %80, %81, %82, %83, %84, %85, %86, %87, %88, %89, %90, %91, %92, %93, %94, %95, %96, %97, %98, %99, %100, %101, %102, %103, %104, %105, %106, %107, %108, %109, %110, %111, %112, %113, %114, %115, %116, %117, %118, %119, %120, %121, %122, %123, %124, %125, %126, %127}, {%128, %129, %130, %131}, db, p, 1, 1, 1;\n}\n"
    : "=f"(d[0]), "=f"(d[1]), "=f"(d[2]), "=f"(d[3]), "=f"(d[4]), "=f"(d[5]), "=f"(d[6]), "=f"(d[7]), "=f"(d[8]), "=f"(d[9]), "=f"(d[10]), "=f"(d[11]), "=f"(d[12]), "=f"(d[13]), "=f"(d[14]), "=f"(d[15]), "=f"(d[16]), "=f"(d[17]), "=f"(d[18]), "=f"(d[19]), "=f"(d[20]), "=f"(d[21]), "=f"(d[22]), "=f"(d[23]), "=f"(d[24]), "=f"(d[25]), "=f"(d[26]), "=f"(d[27]), "=f"(d[28]), "=f"(d[29]), "=f"(d[30]), "=f"(d[31]), "=f"(d[32]), "=f"(d[33]), "=f"(d[34]), "=f"(d[35]), "=f"(d[36]), "=f"(d[37]), "=f"(d[38]), "=f"(d[39]), "=f"(d[40]), "=f"(d[41]), "=f"(d[42]), "=f"(d[43]), "=f"(d[44]), "=f"(d[45]), "=f"(d[46]), "=f"(d[47]), "=f"(d[48]), "=f"(d[49]), "=f"(d[50]), "=f"(d[51]), "=f"(d[52]), "=f"(d[53]), "=f"(d[54]), "=f"(d[55]), "=f"(d[56]), "=f"(d[57]), "=f"(d[58]), "=f"(d[59]), "=f"(d[60]), "=f"(d[61]), "=f"(d[62]), "=f"(d[63]), "=f"(d[64]), "=f"(d[65]), "=f"(d[66]), "=f"(d[67]), "=f"(d[68]), "=f"(d[69]), "=f"(d[70]), "=f"(d[71]), "=f"(d[72]), "=f"(d[73]), "=f"(d[74]), "=f"(d[75]), "=f"(d[76]), "=f"(d[77]), "=f"(d[78]), "=f"(d[79]), "=f"(d[80]), "=f"(d[81]), "=f"(d[82]), "=f"(d[83]), "=f"(d[84]), "=f"(d[85]), "=f"(d[86]), "=f"(d[87]), "=f"(d[88]), "=f"(d[89]), "=f"(d[90]), "=f"(d[91]), "=f"(d[92]), "=f"(d[93]), "=f"(d[94]), "=f"(d[95]), "=f"(d[96]), "=f"(d[97]), "=f"(d[98]), "=f"(d[99]), "=f"(d[100]), "=f"(d[101]), "=f"(d[102]), "=f"(d[103]), "=f"(d[104]), "=f"(d[105]), "=f"(d[106]), "=f"(d[107]), "=f"(d[108]), "=f"(d[109]), "=f"(d[110]), "=f"(d[111]), "=f"(d[112]), "=f"(d[113]), "=f"(d[114]), "=f"(d[115]), "=f"(d[116]), "=f"(d[117]), "=f"(d[118]), "=f"(d[119]), "=f"(d[120]), "=f"(d[121]), "=f"(d[122]), "=f"(d[123]), "=f"(d[124]), "=f"(d[125]), "=f"(d[126]), "=f"(d[127])
    : "r"(a[0]), "r"(a[1]), "r"(a[2]), "r"(a[3]), "r"(db));
  } else {
  asm volatile("{\n.reg .pred p;\n.reg .b64 db;\nsetp.ne.b32 p, 1, 0;\nmov.b64 db, {%132, 0x40000040};\nwgmma.mma_async.sync.aligned.m64n256k16.f32.bf16.bf16 {%0, %1, %2, %3, %4, %5, %6, %7, %8, %9, %10, %11, %12, %13, %14, %15, %16, %17, %18, %19, %20, %21, %22, %23, %24, %25, %26, %27, %28, %29, %30, %31, %32, %33, %34, %35, %36, %37, %38, %39, %40, %41, %42, %43, %44, %45, %46, %47, %48, %49, %50, %51, %52, %53, %54, %55, %56, %57, %58, %59, %60, %61, %62, %63, %64, %65, %66, %67, %68, %69, %70, %71, %72, %73, %74, %75, %76, %77, %78, %79, %80, %81, %82, %83, %84, %85, %86, %87, %88, %89, %90, %91, %92, %93, %94, %95, %96, %97, %98, %99, %100, %101, %102, %103, %104, %105, %106, %107, %108, %109, %110, %111, %112, %113, %114, %115, %116, %117, %118, %119, %120, %121, %122, %123, %124, %125, %126, %127}, {%128, %129, %130, %131}, db, p, 1, 1, 1;\n}\n"
    : "+f"(d[0]), "+f"(d[1]), "+f"(d[2]), "+f"(d[3]), "+f"(d[4]), "+f"(d[5]), "+f"(d[6]), "+f"(d[7]), "+f"(d[8]), "+f"(d[9]), "+f"(d[10]), "+f"(d[11]), "+f"(d[12]), "+f"(d[13]), "+f"(d[14]), "+f"(d[15]), "+f"(d[16]), "+f"(d[17]), "+f"(d[18]), "+f"(d[19]), "+f"(d[20]), "+f"(d[21]), "+f"(d[22]), "+f"(d[23]), "+f"(d[24]), "+f"(d[25]), "+f"(d[26]), "+f"(d[27]), "+f"(d[28]), "+f"(d[29]), "+f"(d[30]), "+f"(d[31]), "+f"(d[32]), "+f"(d[33]), "+f"(d[34]), "+f"(d[35]), "+f"(d[36]), "+f"(d[37]), "+f"(d[38]), "+f"(d[39]), "+f"(d[40]), "+f"(d[41]), "+f"(d[42]), "+f"(d[43]), "+f"(d[44]), "+f"(d[45]), "+f"(d[46]), "+f"(d[47]), "+f"(d[48]), "+f"(d[49]), "+f"(d[50]), "+f"(d[51]), "+f"(d[52]), "+f"(d[53]), "+f"(d[54]), "+f"(d[55]), "+f"(d[56]), "+f"(d[57]), "+f"(d[58]), "+f"(d[59]), "+f"(d[60]), "+f"(d[61]), "+f"(d[62]), "+f"(d[63]), "+f"(d[64]), "+f"(d[65]), "+f"(d[66]), "+f"(d[67]), "+f"(d[68]), "+f"(d[69]), "+f"(d[70]), "+f"(d[71]), "+f"(d[72]), "+f"(d[73]), "+f"(d[74]), "+f"(d[75]), "+f"(d[76]), "+f"(d[77]), "+f"(d[78]), "+f"(d[79]), "+f"(d[80]), "+f"(d[81]), "+f"(d[82]), "+f"(d[83]), "+f"(d[84]), "+f"(d[85]), "+f"(d[86]), "+f"(d[87]), "+f"(d[88]), "+f"(d[89]), "+f"(d[90]), "+f"(d[91]), "+f"(d[92]), "+f"(d[93]), "+f"(d[94]), "+f"(d[95]), "+f"(d[96]), "+f"(d[97]), "+f"(d[98]), "+f"(d[99]), "+f"(d[100]), "+f"(d[101]), "+f"(d[102]), "+f"(d[103]), "+f"(d[104]), "+f"(d[105]), "+f"(d[106]), "+f"(d[107]), "+f"(d[108]), "+f"(d[109]), "+f"(d[110]), "+f"(d[111]), "+f"(d[112]), "+f"(d[113]), "+f"(d[114]), "+f"(d[115]), "+f"(d[116]), "+f"(d[117]), "+f"(d[118]), "+f"(d[119]), "+f"(d[120]), "+f"(d[121]), "+f"(d[122]), "+f"(d[123]), "+f"(d[124]), "+f"(d[125]), "+f"(d[126]), "+f"(d[127])
    : "r"(a[0]), "r"(a[1]), "r"(a[2]), "r"(a[3]), "r"(db));
  }
}
template<bool INIT> __device__ __forceinline__ void wgmma_n128_rs(float* d, const uint32_t* a, uint32_t db) {
  if constexpr (INIT) {
  asm volatile("{\n.reg .pred p;\n.reg .b64 db;\nsetp.ne.b32 p, 0, 0;\nmov.b64 db, {%68, 0x40000040};\nwgmma.mma_async.sync.aligned.m64n128k16.f32.bf16.bf16 {%0, %1, %2, %3, %4, %5, %6, %7, %8, %9, %10, %11, %12, %13, %14, %15, %16, %17, %18, %19, %20, %21, %22, %23, %24, %25, %26, %27, %28, %29, %30, %31, %32, %33, %34, %35, %36, %37, %38, %39, %40, %41, %42, %43, %44, %45, %46, %47, %48, %49, %50, %51, %52, %53, %54, %55, %56, %57, %58, %59, %60, %61, %62, %63}, {%64, %65, %66, %67}, db, p, 1, 1, 1;\n}\n"
    : "=f"(d[0]), "=f"(d[1]), "=f"(d[2]), "=f"(d[3]), "=f"(d[4]), "=f"(d[5]), "=f"(d[6]), "=f"(d[7]), "=f"(d[8]), "=f"(d[9]), "=f"(d[10]), "=f"(d[11]), "=f"(d[12]), "=f"(d[13]), "=f"(d[14]), "=f"(d[15]), "=f"(d[16]), "=f"(d[17]), "=f"(d[18]), "=f"(d[19]), "=f"(d[20]), "=f"(d[21]), "=f"(d[22]), "=f"(d[23]), "=f"(d[24]), "=f"(d[25]), "=f"(d[26]), "=f"(d[27]), "=f"(d[28]), "=f"(d[29]), "=f"(d[30]), "=f"(d[31]), "=f"(d[32]), "=f"(d[33]), "=f"(d[34]), "=f"(d[35]), "=f"(d[36]), "=f"(d[37]), "=f"(d[38]), "=f"(d[39]), "=f"(d[40]), "=f"(d[41]), "=f"(d[42]), "=f"(d[43]), "=f"(d[44]), "=f"(d[45]), "=f"(d[46]), "=f"(d[47]), "=f"(d[48]), "=f"(d[49]), "=f"(d[50]), "=f"(d[51]), "=f"(d[52]), "=f"(d[53]), "=f"(d[54]), "=f"(d[55]), "=f"(d[56]), "=f"(d[57]), "=f"(d[58]), "=f"(d[59]), "=f"(d[60]), "=f"(d[61]), "=f"(d[62]), "=f"(d[63])
    : "r"(a[0]), "r"(a[1]), "r"(a[2]), "r"(a[3]), "r"(db));
  } else {
  asm volatile("{\n.reg .pred p;\n.reg .b64 db;\nsetp.ne.b32 p, 1, 0;\nmov.b64 db, {%68, 0x40000040};\nwgmma.mma_async.sync.aligned.m64n128k16.f32.bf16.bf16 {%0, %1, %2, %3, %4, %5, %6, %7, %8, %9, %10, %11, %12, %13, %14, %15, %16, %17, %18, %19, %20, %21, %22, %23, %24, %25, %26, %27, %28, %29, %30, %31, %32, %33, %34, %35, %36, %37, %38, %39, %40, %41, %42, %43, %44, %45, %46, %47, %48, %49, %50, %51, %52, %53, %54, %55, %56, %57, %58, %59, %60, %61, %62, %63}, {%64, %65, %66, %67}, db, p, 1, 1, 1;\n}\n"
    : "+f"(d[0]), "+f"(d[1]), "+f"(d[2]), "+f"(d[3]), "+f"(d[4]), "+f"(d[5]), "+f"(d[6]), "+f"(d[7]), "+f"(d[8]), "+f"(d[9]), "+f"(d[10]), "+f"(d[11]), "+f"(d[12]), "+f"(d[13]), "+f"(d[14]), "+f"(d[15]), "+f"(d[16]), "+f"(d[17]), "+f"(d[18]), "+f"(d[19]), "+f"(d[20]), "+f"(d[21]), "+f"(d[22]), "+f"(d[23]), "+f"(d[24]), "+f"(d[25]), "+f"(d[26]), "+f"(d[27]), "+f"(d[28]), "+f"(d[29]), "+f"(d[30]), "+f"(d[31]), "+f"(d[32]), "+f"(d[33]), "+f"(d[34]), "+f"(d[35]), "+f"(d[36]), "+f"(d[37]), "+f"(d[38]), "+f"(d[39]), "+f"(d[40]), "+f"(d[41]), "+f"(d[42]), "+f"(d[43]), "+f"(d[44]), "+f"(d[45]), "+f"(d[46]), "+f"(d[47]), "+f"(d[48]), "+f"(d[49]), "+f"(d[50]), "+f"(d[51]), "+f"(d[52]), "+f"(d[53]), "+f"(d[54]), "+f"(d[55]), "+f"(d[56]), "+f"(d[57]), "+f"(d[58]), "+f"(d[59]), "+f"(d[60]), "+f"(d[61]), "+f"(d[62]), "+f"(d[63])
    : "r"(a[0]), "r"(a[1]), "r"(a[2]), "r"(a[3]), "r"(db));
  }
}
template<bool INIT> __device__ __forceinline__ void wgmma_n64_tt(float* d, uint32_t da, uint32_t db) {
  if constexpr (INIT) {
  asm volatile("{\n.reg .pred p;\n.reg .b64 da, db;\nsetp.ne.b32 p, 0, 0;\nmov.b64 da, {%32, 0x40000040};\nmov.b64 db, {%33, 0x40000040};\nwgmma.mma_async.sync.aligned.m64n64k16.f32.bf16.bf16 {%0, %1, %2, %3, %4, %5, %6, %7, %8, %9, %10, %11, %12, %13, %14, %15, %16, %17, %18, %19, %20, %21, %22, %23, %24, %25, %26, %27, %28, %29, %30, %31}, da, db, p, 1, 1, 1, 1;\n}\n"
    : "=f"(d[0]), "=f"(d[1]), "=f"(d[2]), "=f"(d[3]), "=f"(d[4]), "=f"(d[5]), "=f"(d[6]), "=f"(d[7]), "=f"(d[8]), "=f"(d[9]), "=f"(d[10]), "=f"(d[11]), "=f"(d[12]), "=f"(d[13]), "=f"(d[14]), "=f"(d[15]), "=f"(d[16]), "=f"(d[17]), "=f"(d[18]), "=f"(d[19]), "=f"(d[20]), "=f"(d[21]), "=f"(d[22]), "=f"(d[23]), "=f"(d[24]), "=f"(d[25]), "=f"(d[26]), "=f"(d[27]), "=f"(d[28]), "=f"(d[29]), "=f"(d[30]), "=f"(d[31])
    : "r"(da), "r"(db));
  } else {
  asm volatile("{\n.reg .pred p;\n.reg .b64 da, db;\nsetp.ne.b32 p, 1, 0;\nmov.b64 da, {%32, 0x40000040};\nmov.b64 db, {%33, 0x40000040};\nwgmma.mma_async.sync.aligned.m64n64k16.f32.bf16.bf16 {%0, %1, %2, %3, %4, %5, %6, %7, %8, %9, %10, %11, %12, %13, %14, %15, %16, %17, %18, %19, %20, %21, %22, %23, %24, %25, %26, %27, %28, %29, %30, %31}, da, db, p, 1, 1, 1, 1;\n}\n"
    : "+f"(d[0]), "+f"(d[1]), "+f"(d[2]), "+f"(d[3]), "+f"(d[4]), "+f"(d[5]), "+f"(d[6]), "+f"(d[7]), "+f"(d[8]), "+f"(d[9]), "+f"(d[10]), "+f"(d[11]), "+f"(d[12]), "+f"(d[13]), "+f"(d[14]), "+f"(d[15]), "+f"(d[16]), "+f"(d[17]), "+f"(d[18]), "+f"(d[19]), "+f"(d[20]), "+f"(d[21]), "+f"(d[22]), "+f"(d[23]), "+f"(d[24]), "+f"(d[25]), "+f"(d[26]), "+f"(d[27]), "+f"(d[28]), "+f"(d[29]), "+f"(d[30]), "+f"(d[31])
    : "r"(da), "r"(db));
  }
}
template<bool INIT> __device__ __forceinline__ void wgmma_n8_tn(float* d, uint32_t da, uint32_t db) {
  if constexpr (INIT) {
  asm volatile("{\n.reg .pred p;\n.reg .b64 da, db;\nsetp.ne.b32 p, 0, 0;\nmov.b64 da, {%4, 0x40000040};\nmov.b64 db, {%5, 8};\nwgmma.mma_async.sync.aligned.m64n8k16.f32.bf16.bf16 {%0, %1, %2, %3}, da, db, p, 1, 1, 1, 0;\n}\n"
    : "=f"(d[0]), "=f"(d[1]), "=f"(d[2]), "=f"(d[3])
    : "r"(da), "r"(db));
  } else {
  asm volatile("{\n.reg .pred p;\n.reg .b64 da, db;\nsetp.ne.b32 p, 1, 0;\nmov.b64 da, {%4, 0x40000040};\nmov.b64 db, {%5, 8};\nwgmma.mma_async.sync.aligned.m64n8k16.f32.bf16.bf16 {%0, %1, %2, %3}, da, db, p, 1, 1, 1, 0;\n}\n"
    : "+f"(d[0]), "+f"(d[1]), "+f"(d[2]), "+f"(d[3])
    : "r"(da), "r"(db));
  }
}
template<bool INIT> __device__ __forceinline__ void wgmma_n40_tf32(float* d, const uint32_t* a, uint32_t db) {
  if constexpr (INIT) {
  asm volatile("{\n.reg .pred p;\n.reg .b64 db;\nsetp.ne.b32 p, 0, 0;\nmov.b64 db, {%24, 0x40000040};\nwgmma.mma_async.sync.aligned.m64n40k8.f32.tf32.tf32 {%0, %1, %2, %3, %4, %5, %6, %7, %8, %9, %10, %11, %12, %13, %14, %15, %16, %17, %18, %19}, {%20, %21, %22, %23}, db, p, 1, 1;\n}\n"
    : "=f"(d[0]), "=f"(d[1]), "=f"(d[2]), "=f"(d[3]), "=f"(d[4]), "=f"(d[5]), "=f"(d[6]), "=f"(d[7]), "=f"(d[8]), "=f"(d[9]), "=f"(d[10]), "=f"(d[11]), "=f"(d[12]), "=f"(d[13]), "=f"(d[14]), "=f"(d[15]), "=f"(d[16]), "=f"(d[17]), "=f"(d[18]), "=f"(d[19])
    : "r"(a[0]), "r"(a[1]), "r"(a[2]), "r"(a[3]), "r"(db));
  } else {
  asm volatile("{\n.reg .pred p;\n.reg .b64 db;\nsetp.ne.b32 p, 1, 0;\nmov.b64 db, {%24, 0x40000040};\nwgmma.mma_async.sync.aligned.m64n40k8.f32.tf32.tf32 {%0, %1, %2, %3, %4, %5, %6, %7, %8, %9, %10, %11, %12, %13, %14, %15, %16, %17, %18, %19}, {%20, %21, %22, %23}, db, p, 1, 1;\n}\n"
    : "+f"(d[0]), "+f"(d[1]), "+f"(d[2]), "+f"(d[3]), "+f"(d[4]), "+f"(d[5]), "+f"(d[6]), "+f"(d[7]), "+f"(d[8]), "+f"(d[9]), "+f"(d[10]), "+f"(d[11]), "+f"(d[12]), "+f"(d[13]), "+f"(d[14]), "+f"(d[15]), "+f"(d[16]), "+f"(d[17]), "+f"(d[18]), "+f"(d[19])
    : "r"(a[0]), "r"(a[1]), "r"(a[2]), "r"(a[3]), "r"(db));
  }
}

__device__ __forceinline__ void quad_transpose(uint32_t& r0, uint32_t& r1, uint32_t& r2, uint32_t& r3, int c) {
  bool o1 = c & 1, o2 = c & 2;
  uint32_t t0 = o1 ? r0 : r1, t1 = o1 ? r2 : r3;
  t0 = __shfl_xor_sync(~0u, t0, 1); t1 = __shfl_xor_sync(~0u, t1, 1);
  if (o1) { r0 = t0; r2 = t1; } else { r1 = t0; r3 = t1; }
  t0 = o2 ? r0 : r2; t1 = o2 ? r1 : r3;
  t0 = __shfl_xor_sync(~0u, t0, 2); t1 = __shfl_xor_sync(~0u, t1, 2);
  if (o2) { r0 = t0; r1 = t1; } else { r2 = t0; r3 = t1; }
}

__device__ __forceinline__ bool own_tile(int T) { return (0x0D0Cu >> T) & 1; }
__device__ __forceinline__ bool wide_tile(int T) { return (0x3939u >> T) & 1; }

template<int V> struct IntC { static constexpr int value = V; };

__device__ __forceinline__ const CUtensorMap* tile_info(const Params& prm, int T, int j, int rank, int& col) {
  const int tile = T & 7;
  col = 128 * j + 64 * rank;
  if (tile == 0) col = 1024 + 1024 * rank + 128 * j;
  if (tile < 2) return T < 8 ? &prm.wqkv_n : &prm.wqkv_p;
  if (tile == 2) return &prm.wo_p;
  if (tile == 7) return &prm.wd_p;
  col = 448 * j + 128 * (tile - 3);
  return rank ? &prm.wu_p : &prm.wg_p;
}

__device__ __forceinline__ void finish_stats(float4 a, float4 b, float& mean0, float& rstd0, float& mean1, float& rstd1) {
  float ma = a.x + a.z, mb = b.x + b.z;
  ma += __shfl_xor_sync(~0u, ma, 1); mb += __shfl_xor_sync(~0u, mb, 1);
  ma += __shfl_xor_sync(~0u, ma, 2); mb += __shfl_xor_sync(~0u, mb, 2);
  ma *= 0.125f; mb *= 0.125f;
  float va = a.y + a.w + 128.f * ((a.x - ma) * (a.x - ma) + (a.z - ma) * (a.z - ma));
  float vb = b.y + b.w + 128.f * ((b.x - mb) * (b.x - mb) + (b.z - mb) * (b.z - mb));
  va += __shfl_xor_sync(~0u, va, 1); vb += __shfl_xor_sync(~0u, vb, 1);
  va += __shfl_xor_sync(~0u, va, 2); vb += __shfl_xor_sync(~0u, vb, 2);
  mean0 = ma; mean1 = mb;
  rstd0 = rsqrtf(va * (1.f / 1024.f) + 1e-5f); rstd1 = rsqrtf(vb * (1.f / 1024.f) + 1e-5f);
}
__device__ __forceinline__ void tile_stats(const uint32_t* P, float2 (*st)[8], int row, int j, int c) {
  const float p0 = bf_lo(__shfl_sync(~0u, P[0], 0, 4)), p1 = bf_lo(__shfl_sync(~0u, P[4], 0, 4));
  float s0 = 0.f, s1 = 0.f, q0 = 0.f, q1 = 0.f;
#pragma unroll
  for (int b = 0; b < 16; b++) {
    const uint32_t u = P[(b >> 2) * 8 + (b & 3)], v = P[(b >> 2) * 8 + 4 + (b & 3)];
    float a0 = bf_lo(u) - p0, a1 = bf_hi(u) - p0, b0 = bf_lo(v) - p1, b1 = bf_hi(v) - p1;
    s0 += a0 + a1; s1 += b0 + b1;
    q0 = fmaf(a0, a0, fmaf(a1, a1, q0)); q1 = fmaf(b0, b0, fmaf(b1, b1, q1));
  }
  s0 += __shfl_xor_sync(~0u, s0, 1); s1 += __shfl_xor_sync(~0u, s1, 1);
  q0 += __shfl_xor_sync(~0u, q0, 1); q1 += __shfl_xor_sync(~0u, q1, 1);
  s0 += __shfl_xor_sync(~0u, s0, 2); s1 += __shfl_xor_sync(~0u, s1, 2);
  q0 += __shfl_xor_sync(~0u, q0, 2); q1 += __shfl_xor_sync(~0u, q1, 2);
  st_f2_if(&st[row][j], p0 + s0 * (1.f / 128.f), fmaxf(q0 - s0 * s0 * (1.f / 128.f), 0.f), c == 0);
  st_f2_if(&st[row + 8][j], p1 + s1 * (1.f / 128.f), fmaxf(q1 - s1 * s1 * (1.f / 128.f), 0.f), c == 0);
}

__device__ __forceinline__ void pack_half(const float* acc, uint32_t* PK, uint32_t cs_addr, float mean0, float mean1) {
#pragma unroll
  for (int b = 0; b < 16; b++) {
    float2 cs = lds_f2(cs_addr + b * 32);
    const int o = ((b >> 2) & 1) * 16 + (b >> 3) * 4 + (b & 3);
    PK[o] = pack_bf16(fmaf(-mean0, cs.x, acc[4 * b]), fmaf(-mean0, cs.y, acc[4 * b + 1]));
    PK[o + 8] = pack_bf16(fmaf(-mean1, cs.x, acc[4 * b + 2]), fmaf(-mean1, cs.y, acc[4 * b + 3]));
  }
}
__device__ __forceinline__ void pick_unit(uint32_t* t, const uint32_t* PK, int u) {
#define PICK(U) case U: asm volatile("mov.b32 %0, %8;\nmov.b32 %1, %9;\nmov.b32 %2, %10;\nmov.b32 %3, %11;\nmov.b32 %4, %12;\nmov.b32 %5, %13;\nmov.b32 %6, %14;\nmov.b32 %7, %15;" \
    : "=r"(t[0]), "=r"(t[1]), "=r"(t[2]), "=r"(t[3]), "=r"(t[4]), "=r"(t[5]), "=r"(t[6]), "=r"(t[7]) \
    : "r"(PK[8 * U]), "r"(PK[8 * U + 1]), "r"(PK[8 * U + 2]), "r"(PK[8 * U + 3]), "r"(PK[8 * U + 4]), "r"(PK[8 * U + 5]), "r"(PK[8 * U + 6]), "r"(PK[8 * U + 7])); break;
  switch (u) { PICK(1) PICK(2) PICK(3) PICK(4) PICK(5) PICK(6) default: PICK(7) }
#undef PICK
}
__device__ __forceinline__ void load_tile(uint32_t* P, const uint8_t* p0, const uint8_t* p1, uint32_t s2, uint32_t sr) {
#pragma unroll
  for (int q = 0; q < 8; q++) {
    const uint4 a = __ldcg((const uint4*)(((q & 2) ? p1 : p0) + (q >> 2) * s2 + (q & 1) * sr));
    P[4 * q] = a.x; P[4 * q + 1] = a.y; P[4 * q + 2] = a.z; P[4 * q + 3] = a.w;
  }
}
__device__ __forceinline__ void transpose_all(uint32_t* P, int c) {
#pragma unroll
  for (int q = 0; q < 8; q++) quad_transpose(P[4 * q], P[4 * q + 1], P[4 * q + 2], P[4 * q + 3], c);
}
__device__ __forceinline__ void add_residual(uint32_t* P, const float* acc) {
#pragma unroll
  for (int b = 0; b < 16; b++) {
    uint32_t& r0 = P[(b >> 2) * 8 + (b & 3)]; uint32_t& r1 = P[(b >> 2) * 8 + 4 + (b & 3)];
    r0 = pack_bf16(bf_lo(r0) + acc[4 * b], bf_hi(r0) + acc[4 * b + 1]);
    r1 = pack_bf16(bf_lo(r1) + acc[4 * b + 2], bf_hi(r1) + acc[4 * b + 3]);
  }
}
__device__ __forceinline__ float phi_s(float raw, float rstd, float rl2) { return fmaxf(fmaf(raw, rstd, 1.000001f), __saturatef(ex2f(raw * rl2) + 1e-6f)); }

template<bool HELPER>
__device__ __forceinline__ void colsum_warp(const Params& prm, uint32_t sb, uint32_t cbar, int id, int m, int j, int lane, uint32_t epoch) {
  const bool lead = elect_one();
  const int nbox = HELPER ? (id < 16 ? 48 : 40) : 2;
  float acc[8] = {};
#pragma unroll 1
  for (int it = 0; it < 2 * nbox + 1; it++) {
    const int bx = it >> 1, k = it == 0 ? 0 : 1 - (it & 1);
    const int b = it == 0 ? 0 : k ? bx - 1 : bx + 1;
    if (b >= nbox) continue;
    int col, kb = m, mat = 0;
    if (HELPER) {
      const int un = (b >> 3) * 48 + id, ch = un >> 1;
      kb = (un & 1) * 8 + (b & 7);
      if (ch < 16) col = ch * 64;
      else { const int q = ch - 16; mat = 1 + (q & 1); col = q < 96 ? 448 * ((q >> 2) & 7) + 128 * (q >> 5) + 32 * (q & 2) : 448 * ((q - 96) >> 1) + 384; }
    } else {
      col = 1024 + id * 1024 + 128 * j + b * 64;
    }
    const uint32_t sl = b & 1;
    if (k == 0) {
      if (lead) {
        mbar_expect_tx(cbar + 8 * sl, 8192);
        tma_5d(sb + sl * 8192, mat == 0 ? &prm.wqkv_n : mat == 1 ? &prm.wg_p : &prm.wu_p, cbar + 8 * sl, col, kb * 2);
      }
    } else {
      mbar_wait(cbar + 8 * sl, (b >> 1) & 1);
      const uint32_t ad = sb + sl * 8192 + (lane >> 3) * 128;
#pragma unroll 2
      for (int q = 0; q < 8; q++) {
        uint4 v, w;
        asm volatile("ld.shared.v4.u32 {%0, %1, %2, %3}, [%4];" : "=r"(v.x), "=r"(v.y), "=r"(v.z), "=r"(v.w) : "r"(ad + q * 1024 + (((lane & 7) ^ (lane >> 3)) << 4)) : "memory");
        asm volatile("ld.shared.v4.u32 {%0, %1, %2, %3}, [%4];" : "=r"(w.x), "=r"(w.y), "=r"(w.z), "=r"(w.w) : "r"(ad + q * 1024 + 512 + (((lane & 7) ^ (lane >> 3) ^ 4) << 4)) : "memory");
        acc[0] += bf_lo(v.x) + bf_lo(w.x); acc[1] += bf_hi(v.x) + bf_hi(w.x); acc[2] += bf_lo(v.y) + bf_lo(w.y); acc[3] += bf_hi(v.y) + bf_hi(w.y);
        acc[4] += bf_lo(v.z) + bf_lo(w.z); acc[5] += bf_hi(v.z) + bf_hi(w.z); acc[6] += bf_lo(v.w) + bf_lo(w.w); acc[7] += bf_hi(v.w) + bf_hi(w.w);
      }
      __syncwarp();
      if (!HELPER || (b & 7) == 7) {
#pragma unroll
        for (int q = 0; q < 8; q++) { acc[q] += __shfl_xor_sync(~0u, acc[q], 8); acc[q] += __shfl_xor_sync(~0u, acc[q], 16); }
        float* dst = &g_cs[epoch & 1][(mat == 0 ? 0 : mat == 1 ? 3072 : 3072 + F_) + col + 8 * (lane & 7)];
        if (lane < 8) { red_add_v4(dst, acc[0], acc[1], acc[2], acc[3]); red_add_v4(dst + 4, acc[4], acc[5], acc[6], acc[7]); }
#pragma unroll
        for (int q = 0; q < 8; q++) acc[q] = 0.f;
        if (b == nbox - 1 || (HELPER && (b == 7 || b == 31))) {
          __syncwarp();
          if (lead) { fence_gpu(); red_add_u32(&g_cscnt[HELPER ? (b == 7 ? 8 : b == 31 ? 9 : 10) : j][0], 1); }
        }
      }
    }
  }
}

#define TR(i)

__global__ void __launch_bounds__(384, 1) fused_kernel(const __grid_constant__ Params prm) {
  extern __shared__ __align__(1024) uint8_t smem_raw[];
  const uint32_t sbase = __shfl_sync(~0u, smem_u32(smem_raw), 0);
  const uint32_t full = sbase + OFF_BAR, empty = full + 64;
  const uint32_t bar_kvdone = full + 128, bar_kvready = full + 136, bar_sig = full + 144;
  const uint32_t bar_sig2 = full + 160, bar_cs = full + 176;
  const int warp = __shfl_sync(~0u, threadIdx.x >> 5, 0);
  const int rank = blockIdx.x & 1;
  const bool helper = blockIdx.x < 4;
  const int ci = blockIdx.x >> 1, tq = ci - 4;
  const int mp = (ci < 4 || ci >= 64) ? 0 : (tq < 32 ? tq & 7 : 1 + (tq - 32) % 7);
  const int j = ci < 4 ? 2 + ci : ci >= 64 ? ci - 58 : (tq < 32 ? tq >> 3 : 4 + (tq - 32) / 7);
  const int m = mp * 2 + rank;
  const int cta = m * 8 + j;

  if (elect_one()) {
#pragma unroll 1
    for (int t = warp; t < 52; t += 12) mbar_init(full + 8 * t, t < 8 ? 2 : t < 16 ? 4 : t == 16 ? 8 : (t >= 18 && t < 22) ? 4 : 1);
    asm volatile("fence.mbarrier_init.release.cluster;" ::: "memory");
    if (warp < 2) asm volatile("prefetch.tensormap [%0];" :: "l"((uint64_t)(&prm.x + warp)) : "memory");
  }
  __syncwarp();
  asm volatile("barrier.cluster.arrive.relaxed.aligned;" ::: "memory");

  if (helper) {
    cluster_wait();
    colsum_warp<true>(prm, sbase + warp * 16384, full + 224 + warp * 16, blockIdx.x * 12 + warp, 0, 0, lane_id(), load_epoch());
  } else if (warp >= 4) {
    asm volatile("setmaxnreg.inc.sync.aligned.u32 232;");
    const int lane = lane_id();
    const int cw = (warp >> 2) - 1, w4 = warp & 3, g = lane >> 2, c = lane & 3;
    uint32_t PK[64];
    const uint32_t xoff = ((m * 128 + cw * 64 + w4 * 16 + g) * D_ + 128 * j + 8 * c) * 2;
    if (w4 < 2) sts_u32(sbase + OFF_ONES + (w4 * 32 + lane) * 4, 0x3F803F80u);
    cluster_wait();
    load_tile(PK, (const uint8_t*)prm.xin + xoff, (const uint8_t*)prm.xin + xoff + 64, 128, 16 * D_);

    const bool relt = w4 == 0 && lane < 2;
    const uint32_t dones = make_desc(sbase + OFF_ONES, 128);
    {
      const int rloc = cw * 64 + w4 * 16 + g;
      const int row = m * 128 + rloc;
      const uint32_t ioff = rloc * 128 + ((c ^ g) << 4);
      const uint32_t tile_off = (m * 16 + 2 * j) * SLOT;
      const uint32_t da0 = make_desc(sbase + cw * 8192, 16), db0 = make_desc(sbase + SLOT, 8192);
      const uint32_t stg = sbase + OFF_STG + cw * 16384;
      const uint32_t rempty = mapa(empty, lane & 1);
      uint32_t n = 0, pos = 0;
      bool ok = false;
      float mean0, rstd0, mean1, rstd1;
      uint32_t epoch;
      TR(0);
#pragma unroll 1
      for (int T = 0; T < 16; T++) {
        const int layer = T >> 3, tile = T & 7;
        const bool wide = wide_tile(T), own = own_tile(T);
        const int nsteps = tile == 7 ? 56 : 16;
        const bool lnin = tile == 0 || tile == 3;
        float2 (*st)[8] = g_stats[layer * 2 + (tile != 0)];
        if (tile == 3) { pos += 2048; if (pos >= NSLOT * 1024) pos -= NSLOT * 1024; }
        auto run = [&](auto WIDE_) {
          constexpr bool WIDE = decltype(WIDE_)::value;
          float acc[WIDE ? 128 : 64];
          auto kstep = [&](auto FIRST_, auto&& hook) {
            constexpr bool FIRST = decltype(FIRST_)::value;
            if (!ok) mbar_wait(full + 8 * (n & 7), (n >> 3) & 1);
            const uint32_t da = da0 + pos, db = db0 + pos;
            n++;
            wgmma_fence();
#pragma unroll
            for (int kk = 0; kk < 4; kk++) {
              if (FIRST && kk == 0) { if constexpr (WIDE) wgmma_n256_ss<true>(acc, da, db); else wgmma_n128_ss<true>(acc, da, db); }
              else { if constexpr (WIDE) wgmma_n256_ss<false>(acc, da + kk * 2, db + kk * 128); else wgmma_n128_ss<false>(acc, da + kk * 2, db + kk * 128); }
              if (kk == 2) ok = mbar_test(full + 8 * (n & 7), (n >> 3) & 1);
              if (kk == 3) wgmma_commit();
              hook(kk);
            }
            pos += WIDE ? 3072 : 2048; if (pos >= NSLOT * 1024) pos -= NSLOT * 1024;
            if constexpr (!FIRST) {
              wgmma_wait<1>();
              mbar_arrive_remote_if(rempty + 8 * ((n - 2) & 7), relt);
            }
          };
          auto nohook = [](int) {};
          if (own) {
            uint8_t* img = (WIDE ? (tile == 0 ? g_x2 : g_x1) : g_o) + tile_off;
#pragma unroll
            for (int q = 0; q < 8; q++)
              *(uint4*)(img + (q >> 2) * SLOT + (q & 1) * 1024 + (ioff ^ ((q & 2) * 32))) = make_uint4(PK[4 * q], PK[4 * q + 1], PK[4 * q + 2], PK[4 * q + 3]);
            __syncwarp();
            mbar_arrive_if(bar_sig + 8 * cw, lane == 0);
            mbar_wait(full + 8 * (n & 7), (n >> 3) & 1);
            mbar_wait(full + 8 * ((n + 1) & 7), ((n + 1) >> 3) & 1);
            ok = true;
            uint32_t p1 = pos + (WIDE ? 3072 : 2048); if (p1 >= NSLOT * 1024) p1 -= NSLOT * 1024;
#pragma unroll
            for (int q = 0; q < 8; q++)
              sts_v4(sbase + ((q >> 2) ? p1 : pos) * 16 + (q & 1) * 1024 + (ioff ^ ((q & 2) * 32)), make_uint4(PK[4 * q], PK[4 * q + 1], PK[4 * q + 2], PK[4 * q + 3]));
            fence_async_smem();
            wg_bar(1 + cw);
          }
          kstep(IntC<1>{}, nohook);
          int i = 1;
          if (WIDE && lnin) {
            tile_stats(PK, st, row, j, c);
            __syncwarp();
            mbar_arrive_if(bar_sig2 + 8 * cw, lane == 0);
          }
          {
            if (tile >= 4) {
              uint32_t* t = PK;
              const int nu = tile == 7 ? 4 : 8;
              uint8_t* hb = g_h + (m * 56 + (tile - 4) * 16 + (tile == 7 ? j : 2 * j)) * SLOT;
#pragma unroll 1
              for (int u = 0; u < nu; u++) {
                const float rstd = (u & 1) ? rstd1 : rstd0;
                const float ke = rstd * -1.4426950408889634f, iv = rcpf(rstd * rstd);
                kstep(IntC<0>{}, [&](int q) {
                  float s0 = rcpf(fmaf(ex2f(bf_lo(t[q]) * ke), iv, iv)), s1 = rcpf(fmaf(ex2f(bf_hi(t[q]) * ke), iv, iv));
                  t[q] = hmul2(hmul2(t[q], t[4 + q]), pack_bf16(s0, s1));
                });
                *(uint4*)(hb + (u >> 2) * SLOT + (u & 1) * 1024 + (ioff ^ ((u & 2) * 32))) = make_uint4(t[0], t[1], t[2], t[3]);
                pick_unit(t, PK, u + 1);
                i++;
              }
              __syncwarp();
              mbar_arrive_if(bar_sig + 8 * cw, lane == 0);
            }
          }
          if (!WIDE && (tile == 2 || tile == 7)) {
            const uint8_t* rb = T == 2 ? (const uint8_t*)prm.xin : (tile == 2 ? g_x2 : g_x1) + tile_off;
            load_tile(PK, rb + (T == 2 ? xoff : ioff), rb + (T == 2 ? xoff + 64 : ioff ^ 64), T == 2 ? 128 : SLOT, T == 2 ? 16 * D_ : 1024);
          }
#pragma unroll 1
          for (; i < nsteps; i++) {
            if (WIDE && i == 15 && lnin) {
              uint4 sa = __ldcg((const uint4*)&st[row][2 * c]), sb = __ldcg((const uint4*)&st[row + 8][2 * c]);
              PK[0] = sa.x; PK[1] = sa.y; PK[2] = sa.z; PK[3] = sa.w; PK[4] = sb.x; PK[5] = sb.y; PK[6] = sb.z; PK[7] = sb.w;
              if (T == 0) epoch = load_epoch();
            }
            if (cw == 1 && i == nsteps - (WIDE ? 1 : 2)) asm volatile("bar.sync 3, 256;" ::: "memory");
            kstep(IntC<0>{}, nohook);
          }
          if (cw == 0) asm volatile("bar.arrive 3, 256;" ::: "memory");
        if (WIDE && lnin) {
          finish_stats(make_float4(__uint_as_float(PK[0]), __uint_as_float(PK[1]), __uint_as_float(PK[2]), __uint_as_float(PK[3])),
                       make_float4(__uint_as_float(PK[4]), __uint_as_float(PK[5]), __uint_as_float(PK[6]), __uint_as_float(PK[7])), mean0, rstd0, mean1, rstd1);
        }
        if (T < 2 || (WIDE && (tile == 3 || tile == 5))) mbar_wait(bar_cs + 8 * ((tile + 1) >> 1), layer);
        if (!WIDE && T == 2) transpose_all(PK, c);
        wgmma_wait<0>();
        mbar_arrive_remote_if(rempty + 8 * ((n - 1) & 7), relt);
        TR(1 + 2 * T);
        if (!WIDE && (tile == 2 || tile == 7)) add_residual(PK, acc);
        else if (WIDE && tile == 0) {
          const float l0 = rstd0 * 1.4426950408889634f, l1 = rstd1 * 1.4426950408889634f;
          const uint32_t sta = stg + (w4 * 16 + ((lane >> 3) & 1) * 8 + (lane & 7)) * 128, da = make_desc(stg, 8192);
          float kv[2][32], z[2][4];
#pragma unroll
          for (int r = 0; r < 2; r++) {
            uint32_t* t = PK + 32 * r;
#pragma unroll
            for (int b = 0; b < 16; b++) {
              const float2 cs = lds_f2(sbase + OFF_CSQ + ((16 * r + b) * 8 + 2 * c) * 4);
              const float* a = acc + (WIDE ? 64 * r : 0) + 4 * b;
              const float v0 = fmaf(-mean0, cs.x, a[0]), v1 = fmaf(-mean0, cs.y, a[1]), v2 = fmaf(-mean1, cs.x, a[2]), v3 = fmaf(-mean1, cs.y, a[3]);
              if (b < 8) { t[2 * b] = pack_bf16(phi_s(v0, rstd0, l0), phi_s(v1, rstd0, l0)); t[2 * b + 1] = pack_bf16(phi_s(v2, rstd1, l1), phi_s(v3, rstd1, l1)); }
              else { t[2 * b] = pack_bf16(v0 * rstd0, v1 * rstd0); t[2 * b + 1] = pack_bf16(v2 * rstd1, v3 * rstd1); }
            }
            if (r) { wgmma_wait<0>(); wg_bar(1 + cw); }
#pragma unroll
            for (int b = 0; b < 16; b += 2)
              stmatrix_x4(sta + (b >> 3) * 8192 + ((((b & 7) + (lane >> 4)) ^ (lane & 7)) << 4), t[2 * b], t[2 * b + 1], t[2 * b + 2], t[2 * b + 3]);
            fence_async_smem();
            wg_bar(1 + cw);
            wgmma_fence();
            wgmma_n64_tt<true>(kv[r], da + 512, da);
            wgmma_n8_tn<true>(z[r], da, dones);
#pragma unroll
            for (int kk = 1; kk < 4; kk++) {
              wgmma_n64_tt<false>(kv[r], da + 512 + kk * 128, da + kk * 128);
              wgmma_n8_tn<false>(z[r], da + kk * 128, dones);
            }
            wgmma_commit();
          }
          wgmma_wait<0>();
          wg_bar(1 + cw);
          const uint32_t kb = stg + (w4 * 16 + g) * 128 + c * 4;
          float* zd = &g_kv[epoch & 1][layer][j][4096 + (w4 >> 1) * 32 + (w4 & 1) * 16 + (g & 1) * 4 + (g >> 1)];
#pragma unroll
          for (int r = 0; r < 2; r++) {
#pragma unroll
            for (int q = 0; q < 16; q++)
              sts_u32(kb + r * 8192 + (q & 2) * 512 + ((((q >> 2) * 2 + (q & 1)) ^ g) << 4), __float_as_uint(w4 >= 2 ? kv[r][16 + q] : kv[r][q]));
            red_add_f32_if(zd + 64 * r, z[r][0], c == 0); red_add_f32_if(zd + 64 * r + 8, z[r][2], c == 0);
          }
          fence_async_smem();
          __syncwarp();
          mbar_arrive_if(bar_kvdone, lane == 0);
        } else if (WIDE || tile != 1) {
          const uint32_t cs = sbase + OFF_CSGU + (tile - 3) * 1024 + 8 * c;
          pack_half(acc, PK, cs, mean0, mean1);
          if constexpr (WIDE) pack_half(acc + 64, PK + 32, cs + 512, mean0, mean1);
        } else {
          const float l0 = rstd0 * 1.4426950408889634f, l1 = rstd1 * 1.4426950408889634f;
#pragma unroll
          for (int b = 0; b < 16; b++) {
            float2 cs = lds_f2(sbase + OFF_CSQ + (256 + b * 8 + 2 * c) * 4);
            PK[4 * b] = __float_as_uint(phi_s(fmaf(-mean0, cs.x, acc[4 * b]), rstd0, l0));
            PK[4 * b + 1] = __float_as_uint(phi_s(fmaf(-mean1, cs.x, acc[4 * b + 2]), rstd1, l1));
            PK[4 * b + 2] = __float_as_uint(phi_s(fmaf(-mean0, cs.y, acc[4 * b + 1]), rstd0, l0));
            PK[4 * b + 3] = __float_as_uint(phi_s(fmaf(-mean1, cs.y, acc[4 * b + 3]), rstd1, l1));
          }
          mbar_wait(bar_kvready, layer);
          float num[4][20];
          wgmma_fence();
#pragma unroll
          for (int ks = 0; ks < 4; ks++) {
#pragma unroll
            for (int hh = 0; hh < 4; hh++) {
              const uint32_t db = make_desc(sbase + OFF_STG + hh * 5120, 16) + 2 * ks;
              if (ks == 0) wgmma_n40_tf32<true>(num[hh], PK + 16 * hh, db); else wgmma_n40_tf32<false>(num[hh], PK + 16 * hh + 4 * ks, db);
            }
          }
          wgmma_commit();
          wgmma_wait<0>();
#pragma unroll
          for (int hh = 0; hh < 4; hh++) {
            const float* nm = num[hh];
            const float r0 = rcpf(__shfl_sync(~0u, nm[16], 0, 4) + 1e-6f), r1 = rcpf(__shfl_sync(~0u, nm[18], 0, 4) + 1e-6f);
#pragma unroll
            for (int b = 0; b < 4; b++) {
              PK[8 * hh + b] = pack_bf16(nm[4 * b] * r0, nm[4 * b + 1] * r0);
              PK[8 * hh + 4 + b] = pack_bf16(nm[4 * b + 2] * r1, nm[4 * b + 3] * r1);
            }
          }
        }
        };
        if (wide) run(IntC<1>{}); else run(IntC<0>{});
        TR(2 + 2 * T);
      }
      transpose_all(PK, c);
#pragma unroll
      for (int q = 0; q < 8; q++)
        *(uint4*)((uint8_t*)prm.out + xoff + (q >> 1) * 64 + (q & 1) * 16 * D_) = make_uint4(PK[4 * q], PK[4 * q + 1], PK[4 * q + 2], PK[4 * q + 3]);
      if (cta == 0 && threadIdx.x == 128) g_epoch = epoch;
    }
  } else {
    asm volatile("setmaxnreg.dec.sync.aligned.u32 40;");
    const int lane = lane_id();
    cluster_wait();
    uint32_t epoch = 0;
    if (warp >= 2) epoch = load_epoch();
    if (warp >= 2) colsum_warp<false>(prm, sbase + OFF_STG + (warp - 2) * 16384, full + 224 + warp * 16, warp - 2, m, j, lane, epoch);
    if (warp < 2) {
      uint32_t ready = 0, n = 0, dst = sbase;
      const bool lead = elect_one();
#pragma unroll 1
      for (int T = 0; T < 16; T++) {
        const int layer = T >> 3, tile = T & 7;
        const bool own = own_tile(T), wide = wide_tile(T);
        const uint32_t adv = (wide ? 3 : 2) * SLOT, dfill = wide ? 0x40000000u : 0x60000000u;
        uint32_t dtab = tile == 0 ? 0x44444455u : tile == 3 ? 0x44444344u : wide ? 0x44444444u : (tile == 1 || tile == 6) ? 0x66655544u : 0x66666666u;
        if (tile == 3) { dst += 2 * SLOT; if (dst >= sbase + NSLOT * SLOT) dst -= NSLOT * SLOT; }
        int col;
        const CUtensorMap* map = tile_info(prm, T, j, rank, col);
        const int kind = tile < 2 ? 3 : tile == 2 ? 0 : tile < 7 ? 1 : 2;
        const uint8_t* img = kind == 2 ? g_h + m * 56 * SLOT : (kind == 3 ? g_x2 : kind == 0 ? g_o : g_x1) + m * 16 * SLOT;
        const uint32_t* fl = &g_flag[layer][kind][m][lane];
        if ((0x8Du >> tile) & 1) ready = 0;
#pragma unroll 1
        for (int p = 0; p < (tile == 7 ? 28 : 8); p++) {
          const bool dummy = own && p == 0;
          int ab = p, kb, dk = 1;
          uint32_t need;
          if (tile == 7) {
            kb = p < 24 ? 7 * (p & 7) + 2 * (p >> 3) : 14 * p - 330; dk = p < 24 ? 1 : 7;
            need = p < 24 ? 1u << p : 3u << (2 * p - 24);
          } else {
            if (own) ab = p == 0 ? j : (p > j ? p : p - 1);
            kb = 2 * ab;
            need = (dummy || T < 2) ? 0u : 1u << ab;
            if (p == 7 && (tile == 0 || tile == 3)) need |= T ? 0xFFFF : 0xFF00;
          }
          if (n == 4) epoch = load_epoch();
          if (warp && (ready & need) != need) {
            uint32_t tries = 0;
            do {
              ready = __ballot_sync(~0u, ld_acquire(fl) == epoch);
              if (++tries > (1u << 20)) __trap();
            } while ((ready & need) != need);
            fence_async_global();
          }
          const uint8_t* src = img + ab * 2 * SLOT;
#pragma unroll 1
          for (int e = 0; e < 2; e++) {
            const int X = n - (dtab & 15);
            dtab = (dtab >> 4) | dfill;
            const uint32_t fb = full + 8 * (n & 7);
            if (X >= 0) mbar_wait(empty + 8 * (X & 7), (X >> 3) & 1);
            if (lead) {
              if (warp == 0) {
                mbar_expect_tx(fb, adv - SLOT);
                tma_5d_mc(dst + SLOT + rank * 8192, map, fb, col, kb * 2);
                if (wide) tma_5d_mc(dst + 2 * SLOT + rank * 8192, map, fb, col + 64, kb * 2);
              } else if (dummy) {
                mbar_arrive(fb);
              } else {
                mbar_expect_tx(fb, SLOT);
                if (T < 2) tma_2d(dst, &prm.x, fb, kb * 64, m * 128);
                else bulk_load(dst, src, SLOT, fb);
              }
            }
            kb += dk; src += SLOT; n++;
            dst += adv; if (dst >= sbase + NSLOT * SLOT) dst -= NSLOT * SLOT;
          }
        }
      }
    } else {
      const int w = warp - 2;
      {
        float* z = &g_kv[(epoch & 1) ^ 1][0][0][0] + (size_t)cta * 528;
        for (int i = w * 32 + lane; i < 132; i += 64) *(float4*)(z + i * 4) = make_float4(0.f, 0.f, 0.f, 0.f);
        if (w && lane < 20) *(float4*)&g_cs[(epoch & 1) ^ 1][cta * 80 + lane * 4] = make_float4(0.f, 0.f, 0.f, 0.f);
      }
      if (w == 0) {
        int pf = 1;
        uint32_t sigph = 0;
#pragma unroll 1
        for (int ev = 1; ev < 18; ev++) {
          const int layer = ev >= 9, e = ev - 9 * layer;
          const bool se = e == 1 || e == 4;
          const uint32_t sb = se ? bar_sig2 : bar_sig, sp = se ? e >> 2 : sigph;
          const int kind = (0x222211033ull >> (4 * e)) & 3, sub = (0x321010010ull >> (4 * e)) & 3;
          uint32_t* f = &g_flag[layer][kind][m][sub * 8 + j];
          mbar_wait(sb, sp); mbar_wait(sb + 8, sp);
          if (lane == 0) { fence_gpu(); st_relaxed(f, epoch); }
          if (!se) sigph ^= 1;
          const int hi = min(16, layer * 8 + (int)((PFTAB >> (4 * e)) & 15));
#pragma unroll 1
          for (; pf < hi; pf++) {
            int col;
            const CUtensorMap* map = tile_info(prm, pf, j, rank, col);
            const int kb = mp + 8 * (lane >> 1);
            if (kb < ((pf & 7) == 7 ? 56 : 16) && (!(lane & 1) || wide_tile(pf))) tma_5d_prefetch(map, col + 64 * (lane & 1), kb * 2);
          }
          __syncwarp();
        }
      } else {
#pragma unroll 1
        for (int rr = 0; rr < 6; rr++) {
          const int r = rr < 4 ? rr : rr - 2;
          if (r == 2) {
            const int layer = rr >> 2;
            float* kvp = g_kv[epoch & 1][layer][j];
            mbar_wait(bar_kvdone, layer);
            if (lane == 0) {
              bulk_reduce_f32(kvp, sbase + OFF_STG, 16384);
              bulk_reduce_f32(kvp, sbase + OFF_STG + 16384, 16384);
              asm volatile("cp.async.bulk.commit_group;\ncp.async.bulk.wait_group 0;" ::: "memory");
              fence_gpu();
              red_add_u32(&g_kvcnt[layer][j][0], 1);
              mbar_expect_tx(bar_kvready, 16896);
            }
            __syncwarp();
            poll_eq(&g_kvcnt[layer][j][0], epoch * 16);
            fence_async_global();
            if (lane < 8) bulk_load(sbase + OFF_STG + (lane & 3) * 5120 + (lane >> 2) * 4096, kvp + (lane < 4 ? lane * 1024 : 4096 + (lane & 3) * 32), lane < 4 ? 4096 : 128, bar_kvready);
          }
          poll_eq(&g_cscnt[r ? 7 + r : j][0], epoch * (r ? 48 : 32));
          fence_async_global();
          const int nch = (0x6824 >> (4 * r)) & 15, q = lane + (r == 3 ? 8 : 0);
          if (lane == 0) mbar_expect_tx(bar_cs + 8 * r, nch * 256);
          __syncwarp();
          if (lane < nch) {
            const int col = r == 0 ? 1024 + (q & 1) * 1024 + 128 * j + (q >> 1) * 64 : r == 1 ? 128 * j + q * 64 : 3072 + (q & 1) * F_ + 448 * j + (q >> 1) * 64;
            bulk_load(sbase + (r == 0 ? OFF_CSQ : r == 1 ? OFF_CSQ + 1024 : OFF_CSGU) + q * 256, &g_cs[epoch & 1][col], 256, bar_cs + 8 * r);
          }
          __syncwarp();
        }
      }
    }
  }
  __syncwarp();
  cluster_sync();
}

typedef CUresult (*EncodeTiledFn)(CUtensorMap*, CUtensorMapDataType, cuuint32_t, void*, const cuuint64_t*, const cuuint64_t*, const cuuint32_t*, const cuuint32_t*,
                                  CUtensorMapInterleave, CUtensorMapSwizzle, CUtensorMapL2promotion, CUtensorMapFloatOOBfill);

void make_wmap(EncodeTiledFn enc, CUtensorMap* m, const void* ptr, uint64_t rows, uint64_t cols, bool perm) {
  uint64_t rs = cols * 2;
  cuuint64_t gd[5] = {cols, 2, 4, 4, rows / 32};
  cuuint64_t gs[4] = {rs, (perm ? 8 : 2) * rs, (perm ? 2 : 8) * rs, 32 * rs};
  cuuint32_t bd[5] = {64, 2, 4, 4, 2}, es[5] = {1, 1, 1, 1, 1};
  enc(m, CU_TENSOR_MAP_DATA_TYPE_BFLOAT16, 5, (void*)ptr, gd, gs, bd, es, CU_TENSOR_MAP_INTERLEAVE_NONE, CU_TENSOR_MAP_SWIZZLE_128B,
      CU_TENSOR_MAP_L2_PROMOTION_L2_256B, CU_TENSOR_MAP_FLOAT_OOB_FILL_NONE);
}

void make_2d(EncodeTiledFn enc, CUtensorMap* m, const void* ptr, uint64_t rows, uint64_t cols, uint32_t box_rows) {
  cuuint64_t gd[2] = {cols, rows}, gs[1] = {cols * 2}; cuuint32_t bd[2] = {64, box_rows}, es[2] = {1, 1};
  enc(m, CU_TENSOR_MAP_DATA_TYPE_BFLOAT16, 2, (void*)ptr, gd, gs, bd, es, CU_TENSOR_MAP_INTERLEAVE_NONE, CU_TENSOR_MAP_SWIZZLE_128B,
      CU_TENSOR_MAP_L2_PROMOTION_L2_256B, CU_TENSOR_MAP_FLOAT_OOB_FILL_NONE);
}

}

extern "C" void kernel_launch(void* const* d_in, const int* in_sizes, int n_in, void* d_out, int out_size) {
  const __nv_bfloat16* x = (const __nv_bfloat16*)d_in[0];
  const __nv_bfloat16* wqkv = (const __nv_bfloat16*)d_in[1];
  const __nv_bfloat16* wo = (const __nv_bfloat16*)d_in[2];
  const __nv_bfloat16* wg = (const __nv_bfloat16*)d_in[4];
  const __nv_bfloat16* wu = (const __nv_bfloat16*)d_in[5];
  const __nv_bfloat16* wd = (const __nv_bfloat16*)d_in[6];

  void* fn = nullptr; cudaDriverEntryPointQueryResult qr;
  cudaGetDriverEntryPoint("cuTensorMapEncodeTiled", &fn, cudaEnableDefault, &qr);
  EncodeTiledFn enc = (EncodeTiledFn)fn;
  Params prm;
  make_2d(enc, &prm.x, x, S_, D_, 128);
  make_wmap(enc, &prm.wqkv_n, wqkv, D_, 3 * D_, false);
  make_wmap(enc, &prm.wqkv_p, wqkv, D_, 3 * D_, true);
  make_wmap(enc, &prm.wo_p, wo, D_, D_, true);
  make_wmap(enc, &prm.wg_p, wg, D_, F_, true);
  make_wmap(enc, &prm.wu_p, wu, D_, F_, true);
  make_wmap(enc, &prm.wd_p, wd, F_, D_, true);
  prm.xin = x; prm.out = (__nv_bfloat16*)d_out;

  cudaFuncSetAttribute(fused_kernel, cudaFuncAttributeMaxDynamicSharedMemorySize, SMEM_BYTES);
  cudaLaunchConfig_t cfg = {};
  cfg.gridDim = dim3(132); cfg.blockDim = dim3(384); cfg.dynamicSmemBytes = SMEM_BYTES; cfg.stream = cudaStreamPerThread;
  cudaLaunchAttribute at[1];
  at[0].id = cudaLaunchAttributeClusterDimension; at[0].val.clusterDim.x = 2; at[0].val.clusterDim.y = 1; at[0].val.clusterDim.z = 1;
  cfg.attrs = at; cfg.numAttrs = 1;
  cudaLaunchKernelEx(&cfg, fused_kernel, prm);
}
```

```cpp
#include <cuda_runtime.h>
#include <cuda_bf16.h>
#include <cuda.h>
#include <stdint.h>

namespace {

constexpr int S_ = 2048, D_ = 1024, F_ = 3584;
constexpr int NSLOT = 12;
constexpr uint32_t SLOT = 16384;
constexpr uint32_t OFF_STG = NSLOT * SLOT;
constexpr uint32_t OFF_LN = OFF_STG + 32768;
constexpr uint32_t OFF_ONES = OFF_LN + 2048;
constexpr uint32_t OFF_BAR = OFF_ONES + 256;
constexpr uint32_t SMEM_BYTES = OFF_BAR + 512;
constexpr uint32_t OFF_CSKV = OFF_STG + 28672, OFF_CSQ = OFF_STG + 20480, OFF_CSGU = OFF_STG;

struct Scratch {
  uint8_t o[16 * 16 * SLOT], x1[16 * 16 * SLOT], x2[16 * 16 * SLOT], h[16 * 56 * SLOT];
  float2 stats[4][S_][8];
  float cs[2][3072 + 2 * F_];
  float kv[2][2][8][4224];
  uint32_t flag[2][4][16][32];
  uint32_t kvcnt[2][8][32];
  uint32_t cscnt[12][32];
  uint32_t epoch;
};
__device__ __align__(1024) Scratch g_scratch;

struct Params {
  CUtensorMap x, wqkv_n, wqkv_p, wo_p, wg_p, wu_p, wd_p;
  const __nv_bfloat16* xin;
  __nv_bfloat16* out;
  Scratch* sc;
};

__device__ __forceinline__ uint32_t smem_u32(const void* p) { return (uint32_t)__cvta_generic_to_shared(p); }
__device__ __forceinline__ void mbar_init(uint32_t bar, uint32_t count) { asm volatile("mbarrier.init.shared::cta.b64 [%0], %1;" :: "r"(bar), "r"(count) : "memory"); }
__device__ __forceinline__ void mbar_expect_tx(uint32_t bar, uint32_t bytes) { asm volatile("mbarrier.arrive.expect_tx.shared::cta.b64 _, [%0], %1;" :: "r"(bar), "r"(bytes) : "memory"); }
__device__ __forceinline__ void mbar_arrive(uint32_t bar) { asm volatile("mbarrier.arrive.shared::cta.b64 _, [%0];" :: "r"(bar) : "memory"); }
__device__ __forceinline__ void mbar_arrive_cluster(uint32_t bar, uint32_t cta) {
  asm volatile("{\n.reg .b32 ra;\nmapa.shared::cluster.u32 ra, %0, %1;\nmbarrier.arrive.shared::cluster.b64 _, [ra];\n}\n" :: "r"(bar), "r"(cta) : "memory");
}
__device__ __forceinline__ void mbar_arrive_if(uint32_t bar, bool pred) {
  asm volatile("{\n.reg .pred p;\nsetp.ne.b32 p, %1, 0;\n@p mbarrier.arrive.shared::cta.b64 _, [%0];\n}\n" :: "r"(bar), "r"((uint32_t)pred) : "memory");
}
__device__ __forceinline__ void mbar_arrive_remote_if(uint32_t cluster_addr, bool pred) {
  asm volatile("{\n.reg .pred p;\nsetp.ne.b32 p, %1, 0;\n@p mbarrier.arrive.shared::cluster.b64 _, [%0];\n}\n" :: "r"(cluster_addr), "r"((uint32_t)pred) : "memory");
}
__device__ __forceinline__ uint32_t mapa(uint32_t addr, uint32_t cta) { uint32_t r; asm("mapa.shared::cluster.u32 %0, %1, %2;" : "=r"(r) : "r"(addr), "r"(cta)); return r; }
__device__ __forceinline__ void st_f2_if(float2* ptr, float a, float b, bool pred) {
  asm volatile("{\n.reg .pred p;\nsetp.ne.b32 p, %3, 0;\n@p st.global.v2.f32 [%0], {%1, %2};\n}\n" :: "l"(ptr), "f"(a), "f"(b), "r"((uint32_t)pred) : "memory");
}
__device__ __forceinline__ void stg_v4_if(void* ptr, const uint32_t* v, bool pred) {
  asm volatile("{\n.reg .pred p;\nsetp.ne.b32 p, %5, 0;\n@p st.global.v4.u32 [%0], {%1, %2, %3, %4};\n}\n" :: "l"(ptr), "r"(v[0]), "r"(v[1]), "r"(v[2]), "r"(v[3]), "r"((uint32_t)pred) : "memory");
}
__device__ __forceinline__ void red_add_f32_if(float* ptr, float v, bool pred) {
  asm volatile("{\n.reg .pred p;\nsetp.ne.b32 p, %2, 0;\n@p red.relaxed.gpu.global.add.f32 [%0], %1;\n}\n" :: "l"(ptr), "f"(v), "r"((uint32_t)pred) : "memory");
}
__device__ __forceinline__ void mbar_wait(uint32_t bar, uint32_t parity) {
  asm volatile("{\n.reg .pred p;\n.reg .b32 n;\nmov.b32 n, 0;\nWAIT_LOOP:\n"
               "mbarrier.try_wait.parity.shared::cta.b64 p, [%0], %1;\n@p bra WAIT_DONE;\n"
               "add.u32 n, n, 1;\nsetp.lt.u32 p, n, 1048576;\n@p bra WAIT_LOOP;\ntrap;\nWAIT_DONE:\n}\n" :: "r"(bar), "r"(parity) : "memory");
}
__device__ __forceinline__ uint32_t ld_acquire(const uint32_t* p) { uint32_t v; asm volatile("ld.acquire.gpu.global.u32 %0, [%1];" : "=r"(v) : "l"(p) : "memory"); return v; }
__device__ __forceinline__ uint32_t ld_relaxed(const uint32_t* p) { uint32_t v; asm volatile("ld.relaxed.gpu.global.u32 %0, [%1];" : "=r"(v) : "l"(p) : "memory"); return v; }
#define POLL ld_acquire
__device__ __forceinline__ void poll_eq(const uint32_t* p, uint32_t want) {
  uint32_t n = 0;
  while (ld_acquire(p) != want) { if (++n > (1u << 20)) __trap(); }
}
__device__ __forceinline__ void tma_2d(uint32_t dst, const CUtensorMap* m, uint32_t bar, int c0, int c1) {
  asm volatile("cp.async.bulk.tensor.2d.shared::cluster.global.mbarrier::complete_tx::bytes [%0], [%1, {%3, %4}], [%2];"
    :: "r"(dst), "l"((uint64_t)m), "r"(bar), "r"(c0), "r"(c1) : "memory");
}
__device__ __forceinline__ void tma_5d_mc(uint32_t dst, const CUtensorMap* m, uint32_t bar, int c0, int c4) {
  asm volatile("cp.async.bulk.tensor.5d.shared::cluster.global.mbarrier::complete_tx::bytes.multicast::cluster [%0], [%1, {%3, %5, %5, %5, %4}], [%2], %6;"
    :: "r"(dst), "l"((uint64_t)m), "r"(bar), "r"(c0), "r"(c4), "r"(0), "h"((uint16_t)3) : "memory");
}
__device__ __forceinline__ void tma_5d(uint32_t dst, const CUtensorMap* m, uint32_t bar, int c0, int c4) {
  asm volatile("cp.async.bulk.tensor.5d.shared::cluster.global.mbarrier::complete_tx::bytes [%0], [%1, {%3, %5, %5, %5, %4}], [%2];"
    :: "r"(dst), "l"((uint64_t)m), "r"(bar), "r"(c0), "r"(c4), "r"(0) : "memory");
}
__device__ __forceinline__ void tma_5d_prefetch(const CUtensorMap* m, int c0, int c4) {
  asm volatile("cp.async.bulk.prefetch.tensor.5d.L2.global.tile [%0, {%1, %3, %3, %3, %2}];" :: "l"((uint64_t)m), "r"(c0), "r"(c4), "r"(0) : "memory");
}
__device__ __forceinline__ void bulk_load(uint32_t dst, const void* src, uint32_t bytes, uint32_t bar) {
  asm volatile("cp.async.bulk.shared::cluster.global.mbarrier::complete_tx::bytes [%0], [%1], %2, [%3];"
    :: "r"(dst), "l"((uint64_t)src), "r"(bytes), "r"(bar) : "memory");
}
__device__ __forceinline__ void bulk_store(void* dst, uint32_t src, uint32_t bytes) {
  asm volatile("cp.async.bulk.global.shared::cta.bulk_group [%0], [%1], %2;" :: "l"((uint64_t)dst), "r"(src), "r"(bytes) : "memory");
}
#define SKW 1
#define SKN 1
#define KFENCE wgmma_fence()
#define PFSLEEP 500
#define PFTAB 0x988654431ull
#define OWN_FENCE
__device__ __forceinline__ void bulk_reduce_f32(void* dst, uint32_t src, uint32_t bytes) {
  asm volatile("cp.reduce.async.bulk.global.shared::cta.bulk_group.add.f32 [%0], [%1], %2;" :: "l"((uint64_t)dst), "r"(src), "r"(bytes) : "memory");
}
__device__ __forceinline__ void wgmma_fence() { asm volatile("wgmma.fence.sync.aligned;" ::: "memory"); }
__device__ __forceinline__ void wgmma_commit() { asm volatile("wgmma.commit_group.sync.aligned;" ::: "memory"); }
template<int N> __device__ __forceinline__ void wgmma_wait() { asm volatile("wgmma.wait_group.sync.aligned %0;" :: "n"(N) : "memory"); }
__device__ __forceinline__ void cluster_sync() { asm volatile("barrier.cluster.arrive.release.aligned;\nbarrier.cluster.wait.acquire.aligned;" ::: "memory"); }
__device__ __forceinline__ void cluster_wait() { asm volatile("barrier.cluster.wait.acquire.aligned;" ::: "memory"); }
__device__ __forceinline__ void fence_async_smem() { asm volatile("fence.proxy.async.shared::cta;" ::: "memory"); }
__device__ __forceinline__ void fence_async_global() { asm volatile("fence.proxy.async.global;" ::: "memory"); }
__device__ __forceinline__ void fence_gpu() { asm volatile("fence.acq_rel.gpu;" ::: "memory"); }
__device__ __forceinline__ void wg_bar(int id) { asm volatile("bar.sync %0, 128;" :: "r"(id) : "memory"); }
__device__ __forceinline__ void st_relaxed(uint32_t* p, uint32_t v) { asm volatile("st.relaxed.gpu.global.u32 [%0], %1;" :: "l"(p), "r"(v) : "memory"); }
__device__ __forceinline__ void red_add_u32(uint32_t* p, uint32_t v) { asm volatile("red.relaxed.gpu.global.add.u32 [%0], %1;" :: "l"(p), "r"(v) : "memory"); }
__device__ __forceinline__ void red_add_f32(float* p, float v) { asm volatile("red.relaxed.gpu.global.add.f32 [%0], %1;" :: "l"(p), "f"(v) : "memory"); }
__device__ __forceinline__ void red_add_v4(float* p, float a, float b, float c, float d) {
  asm volatile("red.relaxed.gpu.global.add.v4.f32 [%0], {%1, %2, %3, %4};" :: "l"(p), "f"(a), "f"(b), "f"(c), "f"(d) : "memory");
}
__device__ __forceinline__ void stmatrix_x4(uint32_t addr, uint32_t r0, uint32_t r1, uint32_t r2, uint32_t r3) {
  asm volatile("stmatrix.sync.aligned.m8n8.x4.shared.b16 [%0], {%1, %2, %3, %4};" :: "r"(addr), "r"(r0), "r"(r1), "r"(r2), "r"(r3) : "memory");
}
__device__ __forceinline__ float2 lds_f2(uint32_t addr) { float2 v; asm volatile("ld.shared.v2.f32 {%0, %1}, [%2];" : "=f"(v.x), "=f"(v.y) : "r"(addr)); return v; }
__device__ __forceinline__ uint32_t lds_u32(uint32_t addr) { uint32_t v; asm volatile("ld.shared.u32 %0, [%1];" : "=r"(v) : "r"(addr) : "memory"); return v; }
__device__ __forceinline__ void sts_u32(uint32_t addr, uint32_t v) { asm volatile("st.shared.u32 [%0], %1;" :: "r"(addr), "r"(v) : "memory"); }
__device__ __forceinline__ void sts_v4(uint32_t addr, uint4 v) { asm volatile("st.shared.v4.u32 [%0], {%1, %2, %3, %4};" :: "r"(addr), "r"(v.x), "r"(v.y), "r"(v.z), "r"(v.w) : "memory"); }
__device__ __forceinline__ uint32_t pack_bf16(float lo, float hi) { uint32_t r; asm("cvt.rn.bf16x2.f32 %0, %1, %2;" : "=r"(r) : "f"(hi), "f"(lo)); return r; }
__device__ __forceinline__ float bf_lo(uint32_t v) { return __uint_as_float(v << 16); }
__device__ __forceinline__ float bf_hi(uint32_t v) { return __uint_as_float(v & 0xffff0000u); }
__device__ __forceinline__ float ex2f(float x) { float r; asm("ex2.approx.ftz.f32 %0, %1;" : "=f"(r) : "f"(x)); return r; }
__device__ __forceinline__ float rcpf(float x) { float r; asm("rcp.approx.ftz.f32 %0, %1;" : "=f"(r) : "f"(x)); return r; }
__device__ __forceinline__ float phif(float t) { return (t > 0.f ? t + 1.f : ex2f(t * 1.4426950408889634f)) + 1e-6f; }
__device__ __forceinline__ uint32_t make_desc(uint32_t addr, uint32_t lbo) { return ((addr & 0x3FFFF) >> 4) | ((lbo >> 4) << 16); }
__device__ __forceinline__ bool mbar_test(uint32_t bar, uint32_t parity) {
  uint32_t ok;
  asm volatile("{\n.reg .pred p;\nmbarrier.test_wait.parity.shared::cta.b64 p, [%1], %2;\nselp.u32 %0, 1, 0, p;\n}\n" : "=r"(ok) : "r"(bar), "r"(parity) : "memory");
  return ok;
}
__device__ __forceinline__ int lane_id() { int r; asm volatile("mov.u32 %0, %%laneid;" : "=r"(r)); return r; }
#define load_epoch() (__ldcg(&prm.sc->epoch) + 1)
__device__ __forceinline__ bool elect_one() {
  uint32_t r;
  asm volatile("{\n.reg .pred p;\nelect.sync _|p, 0xffffffff;\nselp.u32 %0, 1, 0, p;\n}\n" : "=r"(r));
  return r;
}
__device__ __forceinline__ uint32_t hmul2(uint32_t a, uint32_t b) { uint32_t r; asm("mul.rn.bf16x2 %0, %1, %2;" : "=r"(r) : "r"(a), "r"(b)); return r; }
__device__ __forceinline__ unsigned long long gtime() { unsigned long long t; asm volatile("mov.u64 %0, %%globaltimer;" : "=l"(t)); return t; }

template<bool INIT> __device__ __forceinline__ void wgmma_n256_ss(float* d, uint32_t da, uint32_t db) {
  if constexpr (INIT) {
  asm volatile("{\n.reg .pred p;\n.reg .b64 da, db;\nsetp.ne.b32 p, 0, 0;\nmov.b64 da, {%128, 0x40000040};\nmov.b64 db, {%129, 0x40000040};\nwgmma.mma_async.sync.aligned.m64n256k16.f32.bf16.bf16 {%0, %1, %2, %3, %4, %5, %6, %7, %8, %9, %10, %11, %12, %13, %14, %15, %16, %17, %18, %19, %20, %21, %22, %23, %24, %25, %26, %27, %28, %29, %30, %31, %32, %33, %34, %35, %36, %37, %38, %39, %40, %41, %42, %43, %44, %45, %46, %47, %48, %49, %50, %51, %52, %53, %54, %55, %56, %57, %58, %59, %60, %61, %62, %63, %64, %65, %66, %67, %68, %69, %70, %71, %72, %73, %74, %75, %76, %77, %78, %79, %80, %81, %82, %83, %84, %85, %86, %87, %88, %89, %90, %91, %92, %93, %94, %95, %96, %97, %98, %99, %100, %101, %102, %103, %104, %105, %106, %107, %108, %109, %110, %111, %112, %113, %114, %115, %116, %117, %118, %119, %120, %121, %122, %123, %124, %125, %126, %127}, da, db, p, 1, 1, 0, 1;\n}\n"
    : "=f"(d[0]), "=f"(d[1]), "=f"(d[2]), "=f"(d[3]), "=f"(d[4]), "=f"(d[5]), "=f"(d[6]), "=f"(d[7]), "=f"(d[8]), "=f"(d[9]), "=f"(d[10]), "=f"(d[11]), "=f"(d[12]), "=f"(d[13]), "=f"(d[14]), "=f"(d[15]), "=f"(d[16]), "=f"(d[17]), "=f"(d[18]), "=f"(d[19]), "=f"(d[20]), "=f"(d[21]), "=f"(d[22]), "=f"(d[23]), "=f"(d[24]), "=f"(d[25]), "=f"(d[26]), "=f"(d[27]), "=f"(d[28]), "=f"(d[29]), "=f"(d[30]), "=f"(d[31]), "=f"(d[32]), "=f"(d[33]), "=f"(d[34]), "=f"(d[35]), "=f"(d[36]), "=f"(d[37]), "=f"(d[38]), "=f"(d[39]), "=f"(d[40]), "=f"(d[41]), "=f"(d[42]), "=f"(d[43]), "=f"(d[44]), "=f"(d[45]), "=f"(d[46]), "=f"(d[47]), "=f"(d[48]), "=f"(d[49]), "=f"(d[50]), "=f"(d[51]), "=f"(d[52]), "=f"(d[53]), "=f"(d[54]), "=f"(d[55]), "=f"(d[56]), "=f"(d[57]), "=f"(d[58]), "=f"(d[59]), "=f"(d[60]), "=f"(d[61]), "=f"(d[62]), "=f"(d[63]), "=f"(d[64]), "=f"(d[65]), "=f"(d[66]), "=f"(d[67]), "=f"(d[68]), "=f"(d[69]), "=f"(d[70]), "=f"(d[71]), "=f"(d[72]), "=f"(d[73]), "=f"(d[74]), "=f"(d[75]), "=f"(d[76]), "=f"(d[77]), "=f"(d[78]), "=f"(d[79]), "=f"(d[80]), "=f"(d[81]), "=f"(d[82]), "=f"(d[83]), "=f"(d[84]), "=f"(d[85]), "=f"(d[86]), "=f"(d[87]), "=f"(d[88]), "=f"(d[89]), "=f"(d[90]), "=f"(d[91]), "=f"(d[92]), "=f"(d[93]), "=f"(d[94]), "=f"(d[95]), "=f"(d[96]), "=f"(d[97]), "=f"(d[98]), "=f"(d[99]), "=f"(d[100]), "=f"(d[101]), "=f"(d[102]), "=f"(d[103]), "=f"(d[104]), "=f"(d[105]), "=f"(d[106]), "=f"(d[107]), "=f"(d[108]), "=f"(d[109]), "=f"(d[110]), "=f"(d[111]), "=f"(d[112]), "=f"(d[113]), "=f"(d[114]), "=f"(d[115]), "=f"(d[116]), "=f"(d[117]), "=f"(d[118]), "=f"(d[119]), "=f"(d[120]), "=f"(d[121]), "=f"(d[122]), "=f"(d[123]), "=f"(d[124]), "=f"(d[125]), "=f"(d[126]), "=f"(d[127])
    : "r"(da), "r"(db));
  } else {
  asm volatile("{\n.reg .pred p;\n.reg .b64 da, db;\nsetp.ne.b32 p, 1, 0;\nmov.b64 da, {%128, 0x40000040};\nmov.b64 db, {%129, 0x40000040};\nwgmma.mma_async.sync.aligned.m64n256k16.f32.bf16.bf16 {%0, %1, %2, %3, %4, %5, %6, %7, %8, %9, %10, %11, %12, %13, %14, %15, %16, %17, %18, %19, %20, %21, %22, %23, %24, %25, %26, %27, %28, %29, %30, %31, %32, %33, %34, %35, %36, %37, %38, %39, %40, %41, %42, %43, %44, %45, %46, %47, %48, %49, %50, %51, %52, %53, %54, %55, %56, %57, %58, %59, %60, %61, %62, %63, %64, %65, %66, %67, %68, %69, %70, %71, %72, %73, %74, %75, %76, %77, %78, %79, %80, %81, %82, %83, %84, %85, %86, %87, %88, %89, %90, %91, %92, %93, %94, %95, %96, %97, %98, %99, %100, %101, %102, %103, %104, %105, %106, %107, %108, %109, %110, %111, %112, %113, %114, %115, %116, %117, %118, %119, %120, %121, %122, %123, %124, %125, %126, %127}, da, db, p, 1, 1, 0, 1;\n}\n"
    : "+f"(d[0]), "+f"(d[1]), "+f"(d[2]), "+f"(d[3]), "+f"(d[4]), "+f"(d[5]), "+f"(d[6]), "+f"(d[7]), "+f"(d[8]), "+f"(d[9]), "+f"(d[10]), "+f"(d[11]), "+f"(d[12]), "+f"(d[13]), "+f"(d[14]), "+f"(d[15]), "+f"(d[16]), "+f"(d[17]), "+f"(d[18]), "+f"(d[19]), "+f"(d[20]), "+f"(d[21]), "+f"(d[22]), "+f"(d[23]), "+f"(d[24]), "+f"(d[25]), "+f"(d[26]), "+f"(d[27]), "+f"(d[28]), "+f"(d[29]), "+f"(d[30]), "+f"(d[31]), "+f"(d[32]), "+f"(d[33]), "+f"(d[34]), "+f"(d[35]), "+f"(d[36]), "+f"(d[37]), "+f"(d[38]), "+f"(d[39]), "+f"(d[40]), "+f"(d[41]), "+f"(d[42]), "+f"(d[43]), "+f"(d[44]), "+f"(d[45]), "+f"(d[46]), "+f"(d[47]), "+f"(d[48]), "+f"(d[49]), "+f"(d[50]), "+f"(d[51]), "+f"(d[52]), "+f"(d[53]), "+f"(d[54]), "+f"(d[55]), "+f"(d[56]), "+f"(d[57]), "+f"(d[58]), "+f"(d[59]), "+f"(d[60]), "+f"(d[61]), "+f"(d[62]), "+f"(d[63]), "+f"(d[64]), "+f"(d[65]), "+f"(d[66]), "+f"(d[67]), "+f"(d[68]), "+f"(d[69]), "+f"(d[70]), "+f"(d[71]), "+f"(d[72]), "+f"(d[73]), "+f"(d[74]), "+f"(d[75]), "+f"(d[76]), "+f"(d[77]), "+f"(d[78]), "+f"(d[79]), "+f"(d[80]), "+f"(d[81]), "+f"(d[82]), "+f"(d[83]), "+f"(d[84]), "+f"(d[85]), "+f"(d[86]), "+f"(d[87]), "+f"(d[88]), "+f"(d[89]), "+f"(d[90]), "+f"(d[91]), "+f"(d[92]), "+f"(d[93]), "+f"(d[94]), "+f"(d[95]), "+f"(d[96]), "+f"(d[97]), "+f"(d[98]), "+f"(d[99]), "+f"(d[100]), "+f"(d[101]), "+f"(d[102]), "+f"(d[103]), "+f"(d[104]), "+f"(d[105]), "+f"(d[106]), "+f"(d[107]), "+f"(d[108]), "+f"(d[109]), "+f"(d[110]), "+f"(d[111]), "+f"(d[112]), "+f"(d[113]), "+f"(d[114]), "+f"(d[115]), "+f"(d[116]), "+f"(d[117]), "+f"(d[118]), "+f"(d[119]), "+f"(d[120]), "+f"(d[121]), "+f"(d[122]), "+f"(d[123]), "+f"(d[124]), "+f"(d[125]), "+f"(d[126]), "+f"(d[127])
    : "r"(da), "r"(db));
  }
}
template<bool INIT> __device__ __forceinline__ void wgmma_n128_ss(float* d, uint32_t da, uint32_t db) {
  if constexpr (INIT) {
  asm volatile("{\n.reg .pred p;\n.reg .b64 da, db;\nsetp.ne.b32 p, 0, 0;\nmov.b64 da, {%64, 0x40000040};\nmov.b64 db, {%65, 0x40000040};\nwgmma.mma_async.sync.aligned.m64n128k16.f32.bf16.bf16 {%0, %1, %2, %3, %4, %5, %6, %7, %8, %9, %10, %11, %12, %13, %14, %15, %16, %17, %18, %19, %20, %21, %22, %23, %24, %25, %26, %27, %28, %29, %30, %31, %32, %33, %34, %35, %36, %37, %38, %39, %40, %41, %42, %43, %44, %45, %46, %47, %48, %49, %50, %51, %52, %53, %54, %55, %56, %57, %58, %59, %60, %61, %62, %63}, da, db, p, 1, 1, 0, 1;\n}\n"
    : "=f"(d[0]), "=f"(d[1]), "=f"(d[2]), "=f"(d[3]), "=f"(d[4]), "=f"(d[5]), "=f"(d[6]), "=f"(d[7]), "=f"(d[8]), "=f"(d[9]), "=f"(d[10]), "=f"(d[11]), "=f"(d[12]), "=f"(d[13]), "=f"(d[14]), "=f"(d[15]), "=f"(d[16]), "=f"(d[17]), "=f"(d[18]), "=f"(d[19]), "=f"(d[20]), "=f"(d[21]), "=f"(d[22]), "=f"(d[23]), "=f"(d[24]), "=f"(d[25]), "=f"(d[26]), "=f"(d[27]), "=f"(d[28]), "=f"(d[29]), "=f"(d[30]), "=f"(d[31]), "=f"(d[32]), "=f"(d[33]), "=f"(d[34]), "=f"(d[35]), "=f"(d[36]), "=f"(d[37]), "=f"(d[38]), "=f"(d[39]), "=f"(d[40]), "=f"(d[41]), "=f"(d[42]), "=f"(d[43]), "=f"(d[44]), "=f"(d[45]), "=f"(d[46]), "=f"(d[47]), "=f"(d[48]), "=f"(d[49]), "=f"(d[50]), "=f"(d[51]), "=f"(d[52]), "=f"(d[53]), "=f"(d[54]), "=f"(d[55]), "=f"(d[56]), "=f"(d[57]), "=f"(d[58]), "=f"(d[59]), "=f"(d[60]), "=f"(d[61]), "=f"(d[62]), "=f"(d[63])
    : "r"(da), "r"(db));
  } else {
  asm volatile("{\n.reg .pred p;\n.reg .b64 da, db;\nsetp.ne.b32 p, 1, 0;\nmov.b64 da, {%64, 0x40000040};\nmov.b64 db, {%65, 0x40000040};\nwgmma.mma_async.sync.aligned.m64n128k16.f32.bf16.bf16 {%0, %1, %2, %3, %4, %5, %6, %7, %8, %9, %10, %11, %12, %13, %14, %15, %16, %17, %18, %19, %20, %21, %22, %23, %24, %25, %26, %27, %28, %29, %30, %31, %32, %33, %34, %35, %36, %37, %38, %39, %40, %41, %42, %43, %44, %45, %46, %47, %48, %49, %50, %51, %52, %53, %54, %55, %56, %57, %58, %59, %60, %61, %62, %63}, da, db, p, 1, 1, 0, 1;\n}\n"
    : "+f"(d[0]), "+f"(d[1]), "+f"(d[2]), "+f"(d[3]), "+f"(d[4]), "+f"(d[5]), "+f"(d[6]), "+f"(d[7]), "+f"(d[8]), "+f"(d[9]), "+f"(d[10]), "+f"(d[11]), "+f"(d[12]), "+f"(d[13]), "+f"(d[14]), "+f"(d[15]), "+f"(d[16]), "+f"(d[17]), "+f"(d[18]), "+f"(d[19]), "+f"(d[20]), "+f"(d[21]), "+f"(d[22]), "+f"(d[23]), "+f"(d[24]), "+f"(d[25]), "+f"(d[26]), "+f"(d[27]), "+f"(d[28]), "+f"(d[29]), "+f"(d[30]), "+f"(d[31]), "+f"(d[32]), "+f"(d[33]), "+f"(d[34]), "+f"(d[35]), "+f"(d[36]), "+f"(d[37]), "+f"(d[38]), "+f"(d[39]), "+f"(d[40]), "+f"(d[41]), "+f"(d[42]), "+f"(d[43]), "+f"(d[44]), "+f"(d[45]), "+f"(d[46]), "+f"(d[47]), "+f"(d[48]), "+f"(d[49]), "+f"(d[50]), "+f"(d[51]), "+f"(d[52]), "+f"(d[53]), "+f"(d[54]), "+f"(d[55]), "+f"(d[56]), "+f"(d[57]), "+f"(d[58]), "+f"(d[59]), "+f"(d[60]), "+f"(d[61]), "+f"(d[62]), "+f"(d[63])
    : "r"(da), "r"(db));
  }
}
template<bool INIT> __device__ __forceinline__ void wgmma_n256_nn(float* d, uint32_t da, uint32_t db) {
  if constexpr (INIT) {
  asm volatile("{\n.reg .pred p;\n.reg .b64 da, db;\nsetp.ne.b32 p, 0, 0;\nmov.b64 da, {%128, 8};\nmov.b64 db, {%129, 8};\nwgmma.mma_async.sync.aligned.m64n256k16.f32.bf16.bf16 {%0, %1, %2, %3, %4, %5, %6, %7, %8, %9, %10, %11, %12, %13, %14, %15, %16, %17, %18, %19, %20, %21, %22, %23, %24, %25, %26, %27, %28, %29, %30, %31, %32, %33, %34, %35, %36, %37, %38, %39, %40, %41, %42, %43, %44, %45, %46, %47, %48, %49, %50, %51, %52, %53, %54, %55, %56, %57, %58, %59, %60, %61, %62, %63, %64, %65, %66, %67, %68, %69, %70, %71, %72, %73, %74, %75, %76, %77, %78, %79, %80, %81, %82, %83, %84, %85, %86, %87, %88, %89, %90, %91, %92, %93, %94, %95, %96, %97, %98, %99, %100, %101, %102, %103, %104, %105, %106, %107, %108, %109, %110, %111, %112, %113, %114, %115, %116, %117, %118, %119, %120, %121, %122, %123, %124, %125, %126, %127}, da, db, p, 1, 1, 0, 0;\n}\n"
    : "=f"(d[0]), "=f"(d[1]), "=f"(d[2]), "=f"(d[3]), "=f"(d[4]), "=f"(d[5]), "=f"(d[6]), "=f"(d[7]), "=f"(d[8]), "=f"(d[9]), "=f"(d[10]), "=f"(d[11]), "=f"(d[12]), "=f"(d[13]), "=f"(d[14]), "=f"(d[15]), "=f"(d[16]), "=f"(d[17]), "=f"(d[18]), "=f"(d[19]), "=f"(d[20]), "=f"(d[21]), "=f"(d[22]), "=f"(d[23]), "=f"(d[24]), "=f"(d[25]), "=f"(d[26]), "=f"(d[27]), "=f"(d[28]), "=f"(d[29]), "=f"(d[30]), "=f"(d[31]), "=f"(d[32]), "=f"(d[33]), "=f"(d[34]), "=f"(d[35]), "=f"(d[36]), "=f"(d[37]), "=f"(d[38]), "=f"(d[39]), "=f"(d[40]), "=f"(d[41]), "=f"(d[42]), "=f"(d[43]), "=f"(d[44]), "=f"(d[45]), "=f"(d[46]), "=f"(d[47]), "=f"(d[48]), "=f"(d[49]), "=f"(d[50]), "=f"(d[51]), "=f"(d[52]), "=f"(d[53]), "=f"(d[54]), "=f"(d[55]), "=f"(d[56]), "=f"(d[57]), "=f"(d[58]), "=f"(d[59]), "=f"(d[60]), "=f"(d[61]), "=f"(d[62]), "=f"(d[63]), "=f"(d[64]), "=f"(d[65]), "=f"(d[66]), "=f"(d[67]), "=f"(d[68]), "=f"(d[69]), "=f"(d[70]), "=f"(d[71]), "=f"(d[72]), "=f"(d[73]), "=f"(d[74]), "=f"(d[75]), "=f"(d[76]), "=f"(d[77]), "=f"(d[78]), "=f"(d[79]), "=f"(d[80]), "=f"(d[81]), "=f"(d[82]), "=f"(d[83]), "=f"(d[84]), "=f"(d[85]), "=f"(d[86]), "=f"(d[87]), "=f"(d[88]), "=f"(d[89]), "=f"(d[90]), "=f"(d[91]), "=f"(d[92]), "=f"(d[93]), "=f"(d[94]), "=f"(d[95]), "=f"(d[96]), "=f"(d[97]), "=f"(d[98]), "=f"(d[99]), "=f"(d[100]), "=f"(d[101]), "=f"(d[102]), "=f"(d[103]), "=f"(d[104]), "=f"(d[105]), "=f"(d[106]), "=f"(d[107]), "=f"(d[108]), "=f"(d[109]), "=f"(d[110]), "=f"(d[111]), "=f"(d[112]), "=f"(d[113]), "=f"(d[114]), "=f"(d[115]), "=f"(d[116]), "=f"(d[117]), "=f"(d[118]), "=f"(d[119]), "=f"(d[120]), "=f"(d[121]), "=f"(d[122]), "=f"(d[123]), "=f"(d[124]), "=f"(d[125]), "=f"(d[126]), "=f"(d[127])
    : "r"(da), "r"(db));
  } else {
  asm volatile("{\n.reg .pred p;\n.reg .b64 da, db;\nsetp.ne.b32 p, 1, 0;\nmov.b64 da, {%128, 8};\nmov.b64 db, {%129, 8};\nwgmma.mma_async.sync.aligned.m64n256k16.f32.bf16.bf16 {%0, %1, %2, %3, %4, %5, %6, %7, %8, %9, %10, %11, %12, %13, %14, %15, %16, %17, %18, %19, %20, %21, %22, %23, %24, %25, %26, %27, %28, %29, %30, %31, %32, %33, %34, %35, %36, %37, %38, %39, %40, %41, %42, %43, %44, %45, %46, %47, %48, %49, %50, %51, %52, %53, %54, %55, %56, %57, %58, %59, %60, %61, %62, %63, %64, %65, %66, %67, %68, %69, %70, %71, %72, %73, %74, %75, %76, %77, %78, %79, %80, %81, %82, %83, %84, %85, %86, %87, %88, %89, %90, %91, %92, %93, %94, %95, %96, %97, %98, %99, %100, %101, %102, %103, %104, %105, %106, %107, %108, %109, %110, %111, %112, %113, %114, %115, %116, %117, %118, %119, %120, %121, %122, %123, %124, %125, %126, %127}, da, db, p, 1, 1, 0, 0;\n}\n"
    : "+f"(d[0]), "+f"(d[1]), "+f"(d[2]), "+f"(d[3]), "+f"(d[4]), "+f"(d[5]), "+f"(d[6]), "+f"(d[7]), "+f"(d[8]), "+f"(d[9]), "+f"(d[10]), "+f"(d[11]), "+f"(d[12]), "+f"(d[13]), "+f"(d[14]), "+f"(d[15]), "+f"(d[16]), "+f"(d[17]), "+f"(d[18]), "+f"(d[19]), "+f"(d[20]), "+f"(d[21]), "+f"(d[22]), "+f"(d[23]), "+f"(d[24]), "+f"(d[25]), "+f"(d[26]), "+f"(d[27]), "+f"(d[28]), "+f"(d[29]), "+f"(d[30]), "+f"(d[31]), "+f"(d[32]), "+f"(d[33]), "+f"(d[34]), "+f"(d[35]), "+f"(d[36]), "+f"(d[37]), "+f"(d[38]), "+f"(d[39]), "+f"(d[40]), "+f"(d[41]), "+f"(d[42]), "+f"(d[43]), "+f"(d[44]), "+f"(d[45]), "+f"(d[46]), "+f"(d[47]), "+f"(d[48]), "+f"(d[49]), "+f"(d[50]), "+f"(d[51]), "+f"(d[52]), "+f"(d[53]), "+f"(d[54]), "+f"(d[55]), "+f"(d[56]), "+f"(d[57]), "+f"(d[58]), "+f"(d[59]), "+f"(d[60]), "+f"(d[61]), "+f"(d[62]), "+f"(d[63]), "+f"(d[64]), "+f"(d[65]), "+f"(d[66]), "+f"(d[67]), "+f"(d[68]), "+f"(d[69]), "+f"(d[70]), "+f"(d[71]), "+f"(d[72]), "+f"(d[73]), "+f"(d[74]), "+f"(d[75]), "+f"(d[76]), "+f"(d[77]), "+f"(d[78]), "+f"(d[79]), "+f"(d[80]), "+f"(d[81]), "+f"(d[82]), "+f"(d[83]), "+f"(d[84]), "+f"(d[85]), "+f"(d[86]), "+f"(d[87]), "+f"(d[88]), "+f"(d[89]), "+f"(d[90]), "+f"(d[91]), "+f"(d[92]), "+f"(d[93]), "+f"(d[94]), "+f"(d[95]), "+f"(d[96]), "+f"(d[97]), "+f"(d[98]), "+f"(d[99]), "+f"(d[100]), "+f"(d[101]), "+f"(d[102]), "+f"(d[103]), "+f"(d[104]), "+f"(d[105]), "+f"(d[106]), "+f"(d[107]), "+f"(d[108]), "+f"(d[109]), "+f"(d[110]), "+f"(d[111]), "+f"(d[112]), "+f"(d[113]), "+f"(d[114]), "+f"(d[115]), "+f"(d[116]), "+f"(d[117]), "+f"(d[118]), "+f"(d[119]), "+f"(d[120]), "+f"(d[121]), "+f"(d[122]), "+f"(d[123]), "+f"(d[124]), "+f"(d[125]), "+f"(d[126]), "+f"(d[127])
    : "r"(da), "r"(db));
  }
}
template<bool INIT> __device__ __forceinline__ void wgmma_n128_nn(float* d, uint32_t da, uint32_t db) {
  if constexpr (INIT) {
  asm volatile("{\n.reg .pred p;\n.reg .b64 da, db;\nsetp.ne.b32 p, 0, 0;\nmov.b64 da, {%64, 8};\nmov.b64 db, {%65, 8};\nwgmma.mma_async.sync.aligned.m64n128k16.f32.bf16.bf16 {%0, %1, %2, %3, %4, %5, %6, %7, %8, %9, %10, %11, %12, %13, %14, %15, %16, %17, %18, %19, %20, %21, %22, %23, %24, %25, %26, %27, %28, %29, %30, %31, %32, %33, %34, %35, %36, %37, %38, %39, %40, %41, %42, %43, %44, %45, %46, %47, %48, %49, %50, %51, %52, %53, %54, %55, %56, %57, %58, %59, %60, %61, %62, %63}, da, db, p, 1, 1, 0, 0;\n}\n"
    : "=f"(d[0]), "=f"(d[1]), "=f"(d[2]), "=f"(d[3]), "=f"(d[4]), "=f"(d[5]), "=f"(d[6]), "=f"(d[7]), "=f"(d[8]), "=f"(d[9]), "=f"(d[10]), "=f"(d[11]), "=f"(d[12]), "=f"(d[13]), "=f"(d[14]), "=f"(d[15]), "=f"(d[16]), "=f"(d[17]), "=f"(d[18]), "=f"(d[19]), "=f"(d[20]), "=f"(d[21]), "=f"(d[22]), "=f"(d[23]), "=f"(d[24]), "=f"(d[25]), "=f"(d[26]), "=f"(d[27]), "=f"(d[28]), "=f"(d[29]), "=f"(d[30]), "=f"(d[31]), "=f"(d[32]), "=f"(d[33]), "=f"(d[34]), "=f"(d[35]), "=f"(d[36]), "=f"(d[37]), "=f"(d[38]), "=f"(d[39]), "=f"(d[40]), "=f"(d[41]), "=f"(d[42]), "=f"(d[43]), "=f"(d[44]), "=f"(d[45]), "=f"(d[46]), "=f"(d[47]), "=f"(d[48]), "=f"(d[49]), "=f"(d[50]), "=f"(d[51]), "=f"(d[52]), "=f"(d[53]), "=f"(d[54]), "=f"(d[55]), "=f"(d[56]), "=f"(d[57]), "=f"(d[58]), "=f"(d[59]), "=f"(d[60]), "=f"(d[61]), "=f"(d[62]), "=f"(d[63])
    : "r"(da), "r"(db));
  } else {
  asm volatile("{\n.reg .pred p;\n.reg .b64 da, db;\nsetp.ne.b32 p, 1, 0;\nmov.b64 da, {%64, 8};\nmov.b64 db, {%65, 8};\nwgmma.mma_async.sync.aligned.m64n128k16.f32.bf16.bf16 {%0, %1, %2, %3, %4, %5, %6, %7, %8, %9, %10, %11, %12, %13, %14, %15, %16, %17, %18, %19, %20, %21, %22, %23, %24, %25, %26, %27, %28, %29, %30, %31, %32, %33, %34, %35, %36, %37, %38, %39, %40, %41, %42, %43, %44, %45, %46, %47, %48, %49, %50, %51, %52, %53, %54, %55, %56, %57, %58, %59, %60, %61, %62, %63}, da, db, p, 1, 1, 0, 0;\n}\n"
    : "+f"(d[0]), "+f"(d[1]), "+f"(d[2]), "+f"(d[3]), "+f"(d[4]), "+f"(d[5]), "+f"(d[6]), "+f"(d[7]), "+f"(d[8]), "+f"(d[9]), "+f"(d[10]), "+f"(d[11]), "+f"(d[12]), "+f"(d[13]), "+f"(d[14]), "+f"(d[15]), "+f"(d[16]), "+f"(d[17]), "+f"(d[18]), "+f"(d[19]), "+f"(d[20]), "+f"(d[21]), "+f"(d[22]), "+f"(d[23]), "+f"(d[24]), "+f"(d[25]), "+f"(d[26]), "+f"(d[27]), "+f"(d[28]), "+f"(d[29]), "+f"(d[30]), "+f"(d[31]), "+f"(d[32]), "+f"(d[33]), "+f"(d[34]), "+f"(d[35]), "+f"(d[36]), "+f"(d[37]), "+f"(d[38]), "+f"(d[39]), "+f"(d[40]), "+f"(d[41]), "+f"(d[42]), "+f"(d[43]), "+f"(d[44]), "+f"(d[45]), "+f"(d[46]), "+f"(d[47]), "+f"(d[48]), "+f"(d[49]), "+f"(d[50]), "+f"(d[51]), "+f"(d[52]), "+f"(d[53]), "+f"(d[54]), "+f"(d[55]), "+f"(d[56]), "+f"(d[57]), "+f"(d[58]), "+f"(d[59]), "+f"(d[60]), "+f"(d[61]), "+f"(d[62]), "+f"(d[63])
    : "r"(da), "r"(db));
  }
}
template<bool INIT> __device__ __forceinline__ void wgmma_n64_tt(float* d, uint32_t da, uint32_t db) {
  if constexpr (INIT) {
  asm volatile("{\n.reg .pred p;\n.reg .b64 da, db;\nsetp.ne.b32 p, 0, 0;\nmov.b64 da, {%32, 0x40000040};\nmov.b64 db, {%33, 0x40000040};\nwgmma.mma_async.sync.aligned.m64n64k16.f32.bf16.bf16 {%0, %1, %2, %3, %4, %5, %6, %7, %8, %9, %10, %11, %12, %13, %14, %15, %16, %17, %18, %19, %20, %21, %22, %23, %24, %25, %26, %27, %28, %29, %30, %31}, da, db, p, 1, 1, 1, 1;\n}\n"
    : "=f"(d[0]), "=f"(d[1]), "=f"(d[2]), "=f"(d[3]), "=f"(d[4]), "=f"(d[5]), "=f"(d[6]), "=f"(d[7]), "=f"(d[8]), "=f"(d[9]), "=f"(d[10]), "=f"(d[11]), "=f"(d[12]), "=f"(d[13]), "=f"(d[14]), "=f"(d[15]), "=f"(d[16]), "=f"(d[17]), "=f"(d[18]), "=f"(d[19]), "=f"(d[20]), "=f"(d[21]), "=f"(d[22]), "=f"(d[23]), "=f"(d[24]), "=f"(d[25]), "=f"(d[26]), "=f"(d[27]), "=f"(d[28]), "=f"(d[29]), "=f"(d[30]), "=f"(d[31])
    : "r"(da), "r"(db));
  } else {
  asm volatile("{\n.reg .pred p;\n.reg .b64 da, db;\nsetp.ne.b32 p, 1, 0;\nmov.b64 da, {%32, 0x40000040};\nmov.b64 db, {%33, 0x40000040};\nwgmma.mma_async.sync.aligned.m64n64k16.f32.bf16.bf16 {%0, %1, %2, %3, %4, %5, %6, %7, %8, %9, %10, %11, %12, %13, %14, %15, %16, %17, %18, %19, %20, %21, %22, %23, %24, %25, %26, %27, %28, %29, %30, %31}, da, db, p, 1, 1, 1, 1;\n}\n"
    : "+f"(d[0]), "+f"(d[1]), "+f"(d[2]), "+f"(d[3]), "+f"(d[4]), "+f"(d[5]), "+f"(d[6]), "+f"(d[7]), "+f"(d[8]), "+f"(d[9]), "+f"(d[10]), "+f"(d[11]), "+f"(d[12]), "+f"(d[13]), "+f"(d[14]), "+f"(d[15]), "+f"(d[16]), "+f"(d[17]), "+f"(d[18]), "+f"(d[19]), "+f"(d[20]), "+f"(d[21]), "+f"(d[22]), "+f"(d[23]), "+f"(d[24]), "+f"(d[25]), "+f"(d[26]), "+f"(d[27]), "+f"(d[28]), "+f"(d[29]), "+f"(d[30]), "+f"(d[31])
    : "r"(da), "r"(db));
  }
}
template<bool INIT> __device__ __forceinline__ void wgmma_n8_tn(float* d, uint32_t da, uint32_t db) {
  if constexpr (INIT) {
  asm volatile("{\n.reg .pred p;\n.reg .b64 da, db;\nsetp.ne.b32 p, 0, 0;\nmov.b64 da, {%4, 0x40000040};\nmov.b64 db, {%5, 8};\nwgmma.mma_async.sync.aligned.m64n8k16.f32.bf16.bf16 {%0, %1, %2, %3}, da, db, p, 1, 1, 1, 0;\n}\n"
    : "=f"(d[0]), "=f"(d[1]), "=f"(d[2]), "=f"(d[3])
    : "r"(da), "r"(db));
  } else {
  asm volatile("{\n.reg .pred p;\n.reg .b64 da, db;\nsetp.ne.b32 p, 1, 0;\nmov.b64 da, {%4, 0x40000040};\nmov.b64 db, {%5, 8};\nwgmma.mma_async.sync.aligned.m64n8k16.f32.bf16.bf16 {%0, %1, %2, %3}, da, db, p, 1, 1, 1, 0;\n}\n"
    : "+f"(d[0]), "+f"(d[1]), "+f"(d[2]), "+f"(d[3])
    : "r"(da), "r"(db));
  }
}
template<bool INIT> __device__ __forceinline__ void wgmma_n40_tf32(float* d, const uint32_t* a, uint32_t db) {
  if constexpr (INIT) {
  asm volatile("{\n.reg .pred p;\n.reg .b64 db;\nsetp.ne.b32 p, 0, 0;\nmov.b64 db, {%24, 0x40000040};\nwgmma.mma_async.sync.aligned.m64n40k8.f32.tf32.tf32 {%0, %1, %2, %3, %4, %5, %6, %7, %8, %9, %10, %11, %12, %13, %14, %15, %16, %17, %18, %19}, {%20, %21, %22, %23}, db, p, 1, 1;\n}\n"
    : "=f"(d[0]), "=f"(d[1]), "=f"(d[2]), "=f"(d[3]), "=f"(d[4]), "=f"(d[5]), "=f"(d[6]), "=f"(d[7]), "=f"(d[8]), "=f"(d[9]), "=f"(d[10]), "=f"(d[11]), "=f"(d[12]), "=f"(d[13]), "=f"(d[14]), "=f"(d[15]), "=f"(d[16]), "=f"(d[17]), "=f"(d[18]), "=f"(d[19])
    : "r"(a[0]), "r"(a[1]), "r"(a[2]), "r"(a[3]), "r"(db));
  } else {
  asm volatile("{\n.reg .pred p;\n.reg .b64 db;\nsetp.ne.b32 p, 1, 0;\nmov.b64 db, {%24, 0x40000040};\nwgmma.mma_async.sync.aligned.m64n40k8.f32.tf32.tf32 {%0, %1, %2, %3, %4, %5, %6, %7, %8, %9, %10, %11, %12, %13, %14, %15, %16, %17, %18, %19}, {%20, %21, %22, %23}, db, p, 1, 1;\n}\n"
    : "+f"(d[0]), "+f"(d[1]), "+f"(d[2]), "+f"(d[3]), "+f"(d[4]), "+f"(d[5]), "+f"(d[6]), "+f"(d[7]), "+f"(d[8]), "+f"(d[9]), "+f"(d[10]), "+f"(d[11]), "+f"(d[12]), "+f"(d[13]), "+f"(d[14]), "+f"(d[15]), "+f"(d[16]), "+f"(d[17]), "+f"(d[18]), "+f"(d[19])
    : "r"(a[0]), "r"(a[1]), "r"(a[2]), "r"(a[3]), "r"(db));
  }
}

__device__ __forceinline__ void quad_transpose(uint32_t& r0, uint32_t& r1, uint32_t& r2, uint32_t& r3, int c) {
  bool o1 = c & 1, o2 = c & 2;
  uint32_t t0 = o1 ? r0 : r1, t1 = o1 ? r2 : r3;
  t0 = __shfl_xor_sync(~0u, t0, 1); t1 = __shfl_xor_sync(~0u, t1, 1);
  if (o1) { r0 = t0; r2 = t1; } else { r1 = t0; r3 = t1; }
  t0 = o2 ? r0 : r2; t1 = o2 ? r1 : r3;
  t0 = __shfl_xor_sync(~0u, t0, 2); t1 = __shfl_xor_sync(~0u, t1, 2);
  if (o2) { r0 = t0; r1 = t1; } else { r2 = t0; r3 = t1; }
}

__device__ __forceinline__ bool own_tile(int T) { return (0x0D0Cu >> T) & 1; }
__device__ __forceinline__ bool wide_tile(int T) { return (0x3939u >> T) & 1; }

template<int V> struct IntC { static constexpr int value = V; };

__device__ __forceinline__ const CUtensorMap* tile_info(const Params& prm, int T, int j, int rank, int& col) {
  const int tile = T & 7;
  col = 128 * j + 64 * rank;
  if (tile == 0) col = 1024 + 1024 * rank + 128 * j;
  if (tile < 2) return T < 8 ? &prm.wqkv_n : &prm.wqkv_p;
  if (tile == 2) return &prm.wo_p;
  if (tile == 7) return &prm.wd_p;
  col = 448 * j + 128 * (tile - 3);
  return rank ? &prm.wu_p : &prm.wg_p;
}

__device__ __forceinline__ void split3(float x, uint32_t& a, uint32_t& b, uint32_t& c) {
  a = pack_bf16(0.f, x); x -= __uint_as_float(a);
  b = pack_bf16(0.f, x); x -= __uint_as_float(b);
  c = pack_bf16(0.f, x);
}
__device__ __forceinline__ void tile_stats(const uint32_t* P, float2 (*st)[8], int row, int j, int c) {
  const float p0 = bf_lo(__shfl_sync(~0u, P[0], 0, 4)), p1 = bf_lo(__shfl_sync(~0u, P[4], 0, 4));
  float s0 = 0.f, s1 = 0.f, q0 = 0.f, q1 = 0.f;
#pragma unroll
  for (int b = 0; b < 16; b++) {
    const uint32_t u = P[(b >> 2) * 8 + (b & 3)], v = P[(b >> 2) * 8 + 4 + (b & 3)];
    float a0 = bf_lo(u) - p0, a1 = bf_hi(u) - p0, b0 = bf_lo(v) - p1, b1 = bf_hi(v) - p1;
    s0 += a0 + a1; s1 += b0 + b1;
    q0 = fmaf(a0, a0, fmaf(a1, a1, q0)); q1 = fmaf(b0, b0, fmaf(b1, b1, q1));
  }
  s0 += __shfl_xor_sync(~0u, s0, 1); s1 += __shfl_xor_sync(~0u, s1, 1);
  q0 += __shfl_xor_sync(~0u, q0, 1); q1 += __shfl_xor_sync(~0u, q1, 1);
  s0 += __shfl_xor_sync(~0u, s0, 2); s1 += __shfl_xor_sync(~0u, s1, 2);
  q0 += __shfl_xor_sync(~0u, q0, 2); q1 += __shfl_xor_sync(~0u, q1, 2);
  st_f2_if(&st[row][j], p0 + s0 * (1.f / 128.f), fmaxf(q0 - s0 * s0 * (1.f / 128.f), 0.f), c == 0);
  st_f2_if(&st[row + 8][j], p1 + s1 * (1.f / 128.f), fmaxf(q1 - s1 * s1 * (1.f / 128.f), 0.f), c == 0);
}

__device__ __forceinline__ void pack_half(const float* acc, uint32_t* PK) {
#pragma unroll
  for (int b = 0; b < 16; b++) {
    const int o = ((b >> 2) & 1) * 16 + (b >> 3) * 4 + (b & 3);
    PK[o] = pack_bf16(acc[4 * b], acc[4 * b + 1]);
    PK[o + 8] = pack_bf16(acc[4 * b + 2], acc[4 * b + 3]);
  }
}
template<int N> __device__ __forceinline__ void move_down(uint32_t* PK) {
#pragma unroll
  for (int q = 0; q < N; q++) asm volatile("mov.b32 %0, %1;" : "=r"(PK[q]) : "r"(PK[q + N]));
}
__device__ __forceinline__ void next_unit(uint32_t* PK, int u) {
  if (!(u & 1)) move_down<8>(PK); else if (!(u & 2)) move_down<16>(PK); else move_down<32>(PK);
}
__device__ __forceinline__ void lds_v4(uint32_t* v, uint32_t addr) {
  asm volatile("ld.shared.v4.u32 {%0, %1, %2, %3}, [%4];" : "=r"(v[0]), "=r"(v[1]), "=r"(v[2]), "=r"(v[3]) : "r"(addr) : "memory");
}
__device__ __forceinline__ void lds_tile(uint32_t* P, uint32_t b0, uint32_t b1, uint32_t ioff) {
#pragma unroll
  for (int q = 0; q < 8; q++) lds_v4(P + 4 * q, ((q >> 2) ? b1 : b0) + (q & 1) * 1024 + (ioff ^ ((q & 2) * 32)));
}
__device__ __forceinline__ void transpose_all(uint32_t* P, int c) {
#pragma unroll
  for (int q = 0; q < 8; q++) quad_transpose(P[4 * q], P[4 * q + 1], P[4 * q + 2], P[4 * q + 3], c);
}
__device__ __forceinline__ void add_residual(const uint32_t* P, float* acc) {
#pragma unroll
  for (int b = 0; b < 16; b++) {
    const uint32_t r0 = P[(b >> 2) * 8 + (b & 3)], r1 = P[(b >> 2) * 8 + 4 + (b & 3)];
    acc[4 * b] += bf_lo(r0); acc[4 * b + 1] += bf_hi(r0); acc[4 * b + 2] += bf_lo(r1); acc[4 * b + 3] += bf_hi(r1);
  }
}
__device__ __forceinline__ void pack_tile(uint32_t* P, const float* acc) {
#pragma unroll
  for (int b = 0; b < 16; b++) {
    P[(b >> 2) * 8 + (b & 3)] = pack_bf16(acc[4 * b], acc[4 * b + 1]);
    P[(b >> 2) * 8 + 4 + (b & 3)] = pack_bf16(acc[4 * b + 2], acc[4 * b + 3]);
  }
}
__device__ __forceinline__ float phi_s(float raw, float rstd, float rl2) { return fmaxf(fmaf(raw, rstd, 1.000001f), __saturatef(ex2f(raw * rl2) + 1e-6f)); }

template<bool HELPER>
__device__ __forceinline__ void colsum_warp(const Params& prm, uint32_t sb, uint32_t cbar, int id, int m, int j, int lane, uint32_t epoch) {
  const bool lead = elect_one();
  const int nbox = HELPER ? (id < 16 ? 48 : 40) : 2;
  float acc[8] = {};
  auto unit = [&](int b, int& col, int& kb, int& mat) {
    const int un = (b >> 3) * 48 + id, ch = un >> 1;
    kb = (un & 1) * 8 + (b & 7);
    if (ch < 16) col = ch * 64;
    else { const int q = ch - 16; mat = 1 + (q & 1); col = q < 96 ? 448 * ((q >> 2) & 7) + 128 * (q >> 5) + 32 * (q & 2) : 448 * ((q - 96) >> 1) + 384; }
  };
#pragma unroll 1
  for (int it = 0; it < 2 * nbox + 1; it++) {
    const int bx = it >> 1, k = it == 0 ? 0 : 1 - (it & 1);
    const int b = it == 0 ? 0 : k ? bx - 1 : bx + 1;
    if (b >= nbox) continue;
    int col, kb = m, mat = 0;
    if (HELPER) {
      unit(b, col, kb, mat);
    } else {
      col = 1024 + id * 1024 + 128 * j + b * 64;
    }
    const uint32_t sl = b & 1;
    if (k == 0) {
      if (lead) {
        mbar_expect_tx(cbar + 8 * sl, 8192);
        tma_5d(sb + sl * 8192, mat == 0 ? &prm.wqkv_n : mat == 1 ? &prm.wg_p : &prm.wu_p, cbar + 8 * sl, col, kb * 2);
      }
    } else {
      mbar_wait(cbar + 8 * sl, (b >> 1) & 1);
      const uint32_t ad = sb + sl * 8192 + (lane >> 3) * 128;
#pragma unroll 2
      for (int q = 0; q < 8; q++) {
        uint4 v, w;
        asm volatile("ld.shared.v4.u32 {%0, %1, %2, %3}, [%4];" : "=r"(v.x), "=r"(v.y), "=r"(v.z), "=r"(v.w) : "r"(ad + q * 1024 + (((lane & 7) ^ (lane >> 3)) << 4)) : "memory");
        asm volatile("ld.shared.v4.u32 {%0, %1, %2, %3}, [%4];" : "=r"(w.x), "=r"(w.y), "=r"(w.z), "=r"(w.w) : "r"(ad + q * 1024 + 512 + (((lane & 7) ^ (lane >> 3) ^ 4) << 4)) : "memory");
        acc[0] += bf_lo(v.x) + bf_lo(w.x); acc[1] += bf_hi(v.x) + bf_hi(w.x); acc[2] += bf_lo(v.y) + bf_lo(w.y); acc[3] += bf_hi(v.y) + bf_hi(w.y);
        acc[4] += bf_lo(v.z) + bf_lo(w.z); acc[5] += bf_hi(v.z) + bf_hi(w.z); acc[6] += bf_lo(v.w) + bf_lo(w.w); acc[7] += bf_hi(v.w) + bf_hi(w.w);
      }
      __syncwarp();
      if (!HELPER || (b & 7) == 7) {
#pragma unroll
        for (int q = 0; q < 8; q++) { acc[q] += __shfl_xor_sync(~0u, acc[q], 8); acc[q] += __shfl_xor_sync(~0u, acc[q], 16); }
        float* dst = &prm.sc->cs[epoch & 1][(mat == 0 ? 0 : mat == 1 ? 3072 : 3072 + F_) + col + 8 * (lane & 7)];
        if (lane < 8) { red_add_v4(dst, acc[0], acc[1], acc[2], acc[3]); red_add_v4(dst + 4, acc[4], acc[5], acc[6], acc[7]); }
#pragma unroll
        for (int q = 0; q < 8; q++) acc[q] = 0.f;
        if (b == nbox - 1 || (HELPER && (b < 16 || b == 31))) {
          __syncwarp();
          if (lead) { fence_gpu(); red_add_u32(&prm.sc->cscnt[HELPER ? (b > 31 ? 11 : 8 + ((b + 1) >> 4)) : j][0], 1); }
        }
      }
    }
  }
}

#define TR(i)

__global__ void __launch_bounds__(384, 1) fused_kernel(const __grid_constant__ Params prm) {
  extern __shared__ __align__(1024) uint8_t smem_raw[];
  const uint32_t sbase = __shfl_sync(~0u, smem_u32(smem_raw), 0);
  const uint32_t full = sbase + OFF_BAR, empty = full + 64;
  const uint32_t bar_kvdone = full + 128, bar_kvready = full + 136, bar_sig = full + 144;
  const uint32_t bar_sig2 = full + 160, bar_cs = full + 176, bar_res = full + 216, bar_ln = full + 416;
  const int warp = __shfl_sync(~0u, threadIdx.x >> 5, 0);
  const int rank = blockIdx.x & 1;
  const bool helper = blockIdx.x < 4;
  const int ci = blockIdx.x >> 1, tq = ci - 4;
  const int mp = (ci < 4 || ci >= 64) ? 0 : (tq < 32 ? tq & 7 : 1 + (tq - 32) % 7);
  const int j = ci < 4 ? 2 + ci : ci >= 64 ? ci - 58 : (tq < 32 ? tq >> 3 : 4 + (tq - 32) / 7);
  const int m = mp * 2 + rank;
  const int cta = m * 8 + j;

  if (elect_one()) {
#pragma unroll 1
    for (int t = warp; t < 53; t += 12) mbar_init(full + 8 * t, t < 8 ? 2 : t < 16 ? 4 : t == 16 ? 8 : (t >= 18 && t < 22) ? 4 : 1);
    asm volatile("fence.mbarrier_init.release.cluster;" ::: "memory");
    if (warp < 2) asm volatile("prefetch.tensormap [%0];" :: "l"((uint64_t)(&prm.x + warp)) : "memory");
  }
  __syncwarp();
  asm volatile("barrier.cluster.arrive.relaxed.aligned;" ::: "memory");

  if (helper) {
    cluster_wait();
    colsum_warp<true>(prm, sbase + warp * 16384, full + 224 + warp * 16, blockIdx.x * 12 + warp, 0, 0, lane_id(), load_epoch());
  } else if (warp >= 4) {
    asm volatile("setmaxnreg.inc.sync.aligned.u32 232;");
    const int lane = lane_id();
    const int cw = (warp >> 2) - 1, w4 = warp & 3, g = lane >> 2, c = lane & 3;
    uint32_t PK[64];
    const uint32_t xoff = ((m * 128 + cw * 64 + w4 * 16 + g) * D_ + 128 * j + 8 * c) * 2;
    if (w4 < 2) sts_u32(sbase + OFF_ONES + (w4 * 32 + lane) * 4, 0x3F803F80u);
    cluster_wait();

    const bool relt = w4 == 0 && lane < 2;
    const uint32_t dones = make_desc(sbase + OFF_ONES, 128);
    {
      const int rloc = cw * 64 + w4 * 16 + g;
      const int row = m * 128 + rloc;
      const uint32_t ioff = rloc * 128 + ((c ^ g) << 4);
      const uint32_t tile_off = (m * 16 + 2 * j) * SLOT;
      const uint32_t da0 = make_desc(sbase + cw * 8192, 16), db0 = make_desc(sbase + SLOT, 8192);
      const uint32_t stg = sbase + OFF_STG + cw * 16384;
      const uint32_t rempty = mapa(empty, lane & 1);
      uint32_t n = 0, pos = 0;
      bool ok = false;
      float rstd0, rstd1;
      TR(0);
#pragma unroll 1
      for (int T = 0; T < 16; T++) {
        const int layer = T >> 3, tile = T & 7;
        const bool wide = wide_tile(T), own = own_tile(T);
        const int nsteps = tile == 7 ? 56 : 16;
        const bool lnin = tile == 0 || tile == 3;
        float2 (*st)[8] = prm.sc->stats[layer * 2 + (tile != 0)];
        if (tile == 3) { pos += 2048; if (pos >= NSLOT * 1024) pos -= NSLOT * 1024; }
        auto run = [&](auto WIDE_) {
          constexpr bool WIDE = decltype(WIDE_)::value;
          float acc[WIDE ? 128 : 64];
          auto kstep = [&](auto FIRST_, auto&& hook) {
            constexpr bool FIRST = decltype(FIRST_)::value;
            if (!ok) mbar_wait(full + 8 * (n & 7), (n >> 3) & 1);
            const uint32_t da = da0 + pos, db = db0 + pos;
            n++;
            pos += WIDE ? 3072 : 2048; if (pos >= NSLOT * 1024) pos -= NSLOT * 1024;
            KFENCE;
#pragma unroll
            for (int kk = 0; kk < 4; kk++) {
              if (FIRST && kk == 0) { if constexpr (WIDE) wgmma_n256_ss<true>(acc, da, db); else wgmma_n128_ss<true>(acc, da, db); }
              else { if constexpr (WIDE) wgmma_n256_ss<false>(acc, da + kk * 2, db + kk * 128); else wgmma_n128_ss<false>(acc, da + kk * 2, db + kk * 128); }
              if (kk == 1) {
                if constexpr (!FIRST) {
                  wgmma_commit();
                  wgmma_wait<1>();
                  mbar_arrive_remote_if(rempty + 8 * ((n - 2) & 7), relt);
                }
                ok = mbar_test(full + 8 * (n & 7), (n >> 3) & 1);
              }
              if (kk == 3) wgmma_commit();
              hook(kk);
            }
          };
          auto nohook = [](int) {};
          if (own) {
            uint8_t* img = (WIDE ? (tile == 0 ? prm.sc->x2 : prm.sc->x1) : prm.sc->o) + tile_off;
#pragma unroll
            for (int q = 0; q < 8; q++)
              *(uint4*)(img + (q >> 2) * SLOT + (q & 1) * 1024 + (ioff ^ ((q & 2) * 32))) = make_uint4(PK[4 * q], PK[4 * q + 1], PK[4 * q + 2], PK[4 * q + 3]);
            __syncwarp();
            mbar_arrive_if(bar_sig + 8 * cw, lane == 0);
            mbar_wait(full + 8 * (n & 7), (n >> 3) & 1);
            mbar_wait(full + 8 * ((n + 1) & 7), ((n + 1) >> 3) & 1);
            ok = true;
            uint32_t p1 = pos + (WIDE ? 3072 : 2048); if (p1 >= NSLOT * 1024) p1 -= NSLOT * 1024;
#pragma unroll
            for (int q = 0; q < 8; q++)
              sts_v4(sbase + ((q >> 2) ? p1 : pos) * 16 + (q & 1) * 1024 + (ioff ^ ((q & 2) * 32)), make_uint4(PK[4 * q], PK[4 * q + 1], PK[4 * q + 2], PK[4 * q + 3]));
            fence_async_smem();
            wg_bar(1 + cw);
          }
          kstep(IntC<1>{}, nohook);
          int i = 1;
          if (WIDE && T == 0) { mbar_wait(full + 8, 0); lds_tile(PK, sbase, sbase + 3 * SLOT, ioff); }
          {
            if (tile >= 4) {
              uint32_t* t = PK;
              const int nu = tile == 7 ? 4 : 8;
              uint8_t* hb = prm.sc->h + (m * 56 + (tile - 4) * 16 + (tile == 7 ? j : 2 * j)) * SLOT;
#pragma unroll 1
              for (int u = 0; u < nu; u++) {
                const float rstd = (u & 1) ? rstd1 : rstd0;
                const float ke = rstd * -1.4426950408889634f, iv = rcpf(rstd * rstd);
                kstep(IntC<0>{}, [&](int q) {
                  float s0 = rcpf(fmaf(ex2f(bf_lo(t[q]) * ke), iv, iv)), s1 = rcpf(fmaf(ex2f(bf_hi(t[q]) * ke), iv, iv));
                  t[q] = hmul2(hmul2(t[q], t[4 + q]), pack_bf16(s0, s1));
                });
                *(uint4*)(hb + (u >> 2) * SLOT + (u & 1) * 1024 + (ioff ^ ((u & 2) * 32))) = make_uint4(t[0], t[1], t[2], t[3]);
                next_unit(PK, u);
                i++;
              }
              __syncwarp();
              mbar_arrive_if(bar_sig + 8 * cw, lane == 0);
            }
          }
#pragma unroll 1
          for (; i < nsteps; i++) {
            if (!WIDE && (tile == 2 || tile == 7) && i == (tile == 2 ? 2 : 12 + 2 * cw)) {
              mbar_wait(bar_res, tile & 1);
              lds_tile(PK, sbase + OFF_STG, sbase + OFF_STG + SLOT, ioff);
              if (T == 2) transpose_all(PK, c);
              wgmma_wait<0>();
              add_residual(PK, acc);
            }
            if (WIDE && lnin && i == 2) {
              tile_stats(PK, st, row, j, c);
              __syncwarp();
              mbar_arrive_if(bar_sig2 + 8 * cw, lane == 0);
            }
            if (cw == 1 && i == nsteps - (WIDE ? SKW : SKN)) asm volatile("bar.sync 3, 256;" ::: "memory");
            kstep(IntC<0>{}, nohook);
          }
          if (WIDE || tile == 1 || tile == 6) {
            if (WIDE && lnin) mbar_wait(bar_ln, tile != 0);
            if (tile != 6) mbar_wait(bar_cs + 8 * (tile - (tile > 2)), layer);
            const uint32_t dc = make_desc(sbase + (tile == 0 ? OFF_CSKV : tile == 1 ? OFF_CSQ : OFF_CSGU + (tile - 3) * 4096), 0);
            wgmma_fence();
            if constexpr (WIDE) wgmma_n256_nn<false>(acc, make_desc(sbase + OFF_LN + cw * 1024, 0), dc); else wgmma_n128_nn<false>(acc, make_desc(sbase + OFF_LN + cw * 1024, 0), dc);
            wgmma_commit();
            if (WIDE && lnin) {
              const uint32_t r0 = lds_u32(sbase + OFF_LN + rloc * 16 + 12), r1 = lds_u32(sbase + OFF_LN + rloc * 16 + 140);
              rstd0 = bf_lo(r0) + bf_hi(r0); rstd1 = bf_lo(r1) + bf_hi(r1);
            }
          }
          if (cw == 0) asm volatile("bar.arrive 3, 256;" ::: "memory");
        wgmma_wait<0>();
        mbar_arrive_remote_if(rempty + 8 * ((n - 1) & 7), relt);
        TR(1 + 2 * T);
        if (!WIDE && (tile == 2 || tile == 7)) pack_tile(PK, acc);
        else if (WIDE && tile == 0) {
          const float l0 = rstd0 * 1.4426950408889634f, l1 = rstd1 * 1.4426950408889634f;
          const uint32_t sta = stg + (w4 * 16 + ((lane >> 3) & 1) * 8 + (lane & 7)) * 128, da = make_desc(stg, 8192);
          float kv[2][32], z[2][4];
#pragma unroll
          for (int r = 0; r < 2; r++) {
            uint32_t* t = PK + 32 * r;
#pragma unroll
            for (int b = 0; b < 16; b++) {
              const float* a = acc + (WIDE ? 64 * r : 0) + 4 * b;
              const float v0 = a[0], v1 = a[1], v2 = a[2], v3 = a[3];
              if (b < 8) { t[2 * b] = pack_bf16(phi_s(v0, rstd0, l0), phi_s(v1, rstd0, l0)); t[2 * b + 1] = pack_bf16(phi_s(v2, rstd1, l1), phi_s(v3, rstd1, l1)); }
              else { t[2 * b] = pack_bf16(v0 * rstd0, v1 * rstd0); t[2 * b + 1] = pack_bf16(v2 * rstd1, v3 * rstd1); }
            }
            if (r) { wgmma_wait<0>(); wg_bar(1 + cw); }
#pragma unroll
            for (int b = 0; b < 16; b += 2)
              stmatrix_x4(sta + (b >> 3) * 8192 + ((((b & 7) + (lane >> 4)) ^ (lane & 7)) << 4), t[2 * b], t[2 * b + 1], t[2 * b + 2], t[2 * b + 3]);
            fence_async_smem();
            wg_bar(1 + cw);
            wgmma_fence();
            wgmma_n64_tt<true>(kv[r], da + 512, da);
            wgmma_n8_tn<true>(z[r], da, dones);
#pragma unroll
            for (int kk = 1; kk < 4; kk++) {
              wgmma_n64_tt<false>(kv[r], da + 512 + kk * 128, da + kk * 128);
              wgmma_n8_tn<false>(z[r], da + kk * 128, dones);
            }
            wgmma_commit();
          }
          wgmma_wait<0>();
          wg_bar(1 + cw);
          const uint32_t kb = stg + (w4 * 16 + g) * 128 + c * 4;
          float* zd = &prm.sc->kv[lds_u32(full + 480) & 1][layer][j][4096 + (w4 >> 1) * 32 + (w4 & 1) * 16 + (g & 1) * 4 + (g >> 1)];
#pragma unroll
          for (int r = 0; r < 2; r++) {
#pragma unroll
            for (int q = 0; q < 16; q++)
              sts_u32(kb + r * 8192 + (q & 2) * 512 + ((((q >> 2) * 2 + (q & 1)) ^ g) << 4), __float_as_uint(w4 >= 2 ? kv[r][16 + q] : kv[r][q]));
            red_add_f32_if(zd + 64 * r, z[r][0], c == 0); red_add_f32_if(zd + 64 * r + 8, z[r][2], c == 0);
          }
          fence_async_smem();
          __syncwarp();
          mbar_arrive_if(bar_kvdone, lane == 0);
        } else if (WIDE || tile != 1) {
          pack_half(acc, PK);
          if constexpr (WIDE) pack_half(acc + 64, PK + 32);
        } else {
          const float l0 = rstd0 * 1.4426950408889634f, l1 = rstd1 * 1.4426950408889634f;
#pragma unroll
          for (int b = 0; b < 16; b++) {
            PK[4 * b] = __float_as_uint(phi_s(acc[4 * b], rstd0, l0));
            PK[4 * b + 1] = __float_as_uint(phi_s(acc[4 * b + 2], rstd1, l1));
            PK[4 * b + 2] = __float_as_uint(phi_s(acc[4 * b + 1], rstd0, l0));
            PK[4 * b + 3] = __float_as_uint(phi_s(acc[4 * b + 3], rstd1, l1));
          }
          mbar_wait(bar_kvready, layer);
          float num[4][20];
          wgmma_fence();
#pragma unroll
          for (int ks = 0; ks < 4; ks++) {
#pragma unroll
            for (int hh = 0; hh < 4; hh++) {
              const uint32_t db = make_desc(sbase + OFF_STG + hh * 5120, 16) + 2 * ks;
              if (ks == 0) wgmma_n40_tf32<true>(num[hh], PK + 16 * hh, db); else wgmma_n40_tf32<false>(num[hh], PK + 16 * hh + 4 * ks, db);
            }
          }
          wgmma_commit();
          wgmma_wait<0>();
#pragma unroll
          for (int hh = 0; hh < 4; hh++) {
            const float* nm = num[hh];
            const float r0 = rcpf(__shfl_sync(~0u, nm[16], 0, 4) + 1e-6f), r1 = rcpf(__shfl_sync(~0u, nm[18], 0, 4) + 1e-6f);
#pragma unroll
            for (int b = 0; b < 4; b++) {
              PK[8 * hh + b] = pack_bf16(nm[4 * b] * r0, nm[4 * b + 1] * r0);
              PK[8 * hh + 4 + b] = pack_bf16(nm[4 * b + 2] * r1, nm[4 * b + 3] * r1);
            }
          }
        }
        };
        if (wide) run(IntC<1>{}); else run(IntC<0>{});
        TR(2 + 2 * T);
      }
      asm volatile("barrier.cluster.arrive.relaxed.aligned;" ::: "memory");
      transpose_all(PK, c);
#pragma unroll
      for (int q = 0; q < 8; q++)
        *(uint4*)((uint8_t*)prm.out + xoff + (q >> 1) * 64 + (q & 1) * 16 * D_) = make_uint4(PK[4 * q], PK[4 * q + 1], PK[4 * q + 2], PK[4 * q + 3]);
      if (cta == 0 && threadIdx.x == 128) prm.sc->epoch = lds_u32(full + 480);
    }
  } else {
    asm volatile("setmaxnreg.dec.sync.aligned.u32 40;");
    const int lane = lane_id();
    cluster_wait();
    uint32_t epoch = 0;
    if (warp >= 2) { epoch = load_epoch(); sts_u32(full + 480, epoch); mbar_wait(full, 0); }
    if (warp >= 2) colsum_warp<false>(prm, sbase + OFF_STG + (warp - 2) * 16384, full + 224 + warp * 16, warp - 2, m, j, lane, epoch);
    if (warp < 2) {
      uint32_t ready = 0, n = 0, dst = sbase;
      const bool lead = elect_one();
#pragma unroll 1
      for (int T = 0; T < 16; T++) {
        const int layer = T >> 3, tile = T & 7;
        const bool own = own_tile(T), wide = wide_tile(T);
        const uint32_t adv = (wide ? 3 : 2) * SLOT, dfill = wide ? 0x40000000u : 0x60000000u;
        uint32_t dtab = tile == 0 ? 0x44444455u : tile == 3 ? 0x44444344u : wide ? 0x44444444u : (tile == 1 || tile == 6) ? 0x66655544u : 0x66666666u;
        if (tile == 3) { dst += 2 * SLOT; if (dst >= sbase + NSLOT * SLOT) dst -= NSLOT * SLOT; }
        int col;
        const CUtensorMap* map = tile_info(prm, T, j, rank, col);
        const int kind = tile < 2 ? 3 : tile == 2 ? 0 : tile < 7 ? 1 : 2;
        const uint8_t* img = kind == 2 ? prm.sc->h + m * 56 * SLOT : (kind == 3 ? prm.sc->x2 : kind == 0 ? prm.sc->o : prm.sc->x1) + m * 16 * SLOT;
        const uint32_t* fl = &prm.sc->flag[layer][kind][m][lane];
        if ((0x8Du >> tile) & 1) ready = 0;
#pragma unroll 1
        for (int p = 0; p < (tile == 7 ? 28 : 8); p++) {
          const bool dummy = own && p == 0;
          int ab = p, kb, dk = 1;
          uint32_t need;
          if (tile == 7) {
            kb = p < 24 ? 7 * (p & 7) + 2 * (p >> 3) : 14 * p - 330; dk = p < 24 ? 1 : 7;
            need = p < 24 ? 1u << p : 3u << (2 * p - 24);
          } else {
            if (own || T == 0) ab = p == 0 ? j : (p > j ? p : p - 1);
            kb = 2 * ab;
            need = (dummy || T < 2) ? 0u : 1u << ab;
          }
          if (n == 4) epoch = load_epoch();
          if (warp && (ready & need) != need) {
            uint32_t tries = 0;
            do {
              ready = __ballot_sync(~0u, POLL(fl) == epoch);
              if (++tries > (1u << 20)) __trap();
            } while ((ready & need) != need);
            fence_async_global();
          }
          const uint8_t* src = img + ab * 2 * SLOT;
#pragma unroll 1
          for (int e = 0; e < 2; e++) {
            const int X = n - (dtab & 15);
            dtab = (dtab >> 4) | dfill;
            const uint32_t fb = full + 8 * (n & 7);
            if (X >= 0) mbar_wait(empty + 8 * (X & 7), (X >> 3) & 1);
            if (lead) {
              if (warp == 0) {
                mbar_expect_tx(fb, adv - SLOT);
                tma_5d_mc(dst + SLOT + rank * 8192, map, fb, col, kb * 2);
                if (wide) tma_5d_mc(dst + 2 * SLOT + rank * 8192, map, fb, col + 64, kb * 2);
              } else if (dummy) {
                mbar_arrive(fb);
              } else {
                mbar_expect_tx(fb, SLOT);
                if (T < 2) tma_2d(dst, &prm.x, fb, kb * 64, m * 128);
                else bulk_load(dst, src, SLOT, fb);
              }
            }
            kb += dk; src += SLOT; n++;
            dst += adv; if (dst >= sbase + NSLOT * SLOT) dst -= NSLOT * SLOT;
          }
        }
      }
    } else {
      const int w = warp - 2;
      {
        float* z = &prm.sc->kv[(epoch & 1) ^ 1][0][0][0] + (size_t)cta * 528;
        for (int i = w * 32 + lane; i < 132; i += 64) *(float4*)(z + i * 4) = make_float4(0.f, 0.f, 0.f, 0.f);
        if (w && lane < 20) *(float4*)&prm.sc->cs[(epoch & 1) ^ 1][cta * 80 + lane * 4] = make_float4(0.f, 0.f, 0.f, 0.f);
      }
      if (w == 0) {
        int pf = 1;
        uint32_t sigph = 0;
#pragma unroll 1
        for (int ev = 1; ev < 18; ev++) {
          const int layer = ev >= 9, e = ev - 9 * layer;
          const bool se = e == 1 || e == 4;
          const uint32_t sb = se ? bar_sig2 : bar_sig, sp = se ? e >> 2 : sigph;
          const int kind = (0x222211033ull >> (4 * e)) & 3, sub = (0x321010010ull >> (4 * e)) & 3;
          uint32_t* f = &prm.sc->flag[layer][kind][m][sub * 8 + j];
          mbar_wait(sb, sp); mbar_wait(sb + 8, sp);
          if ((e == 2 || e == 8) && lane == 0) {
            fence_async_global();
            mbar_expect_tx(bar_res, 2 * SLOT);
            if (ev == 2) { tma_2d(sbase + OFF_STG, &prm.x, bar_res, 128 * j, m * 128); tma_2d(sbase + OFF_STG + SLOT, &prm.x, bar_res, 128 * j + 64, m * 128); }
            else bulk_load(sbase + OFF_STG, (e == 2 ? prm.sc->x2 : prm.sc->x1) + (m * 16 + 2 * j) * SLOT, 2 * SLOT, bar_res);
          }
          if (lane == 0) { fence_gpu(); st_relaxed(f, epoch); }
          if (!se) sigph ^= 1;
          const int hi = min(16, layer * 8 + (int)((PFTAB >> (4 * e)) & 15));
#pragma unroll 1
          for (; pf < hi; pf++) {
            int col;
            const CUtensorMap* map = tile_info(prm, pf, j, rank, col);
#pragma unroll 1
            for (int kb = mp; kb < ((pf & 7) == 7 ? 56 : 16); kb += 8) {
              if (lane == 0) { tma_5d_prefetch(map, col, kb * 2); if (wide_tile(pf)) tma_5d_prefetch(map, col + 64, kb * 2); }
              __nanosleep(PFSLEEP);
            }
          }
          __syncwarp();
        }
      } else {
#pragma unroll 1
        for (int rr = 0; rr < 10; rr++) {
          const int layer = rr >= 5, r = rr - 5 * layer;
          const bool lnr = r == 0 || r == 2;
          if (lnr) { mbar_wait(bar_sig2, r >> 1); mbar_wait(bar_sig2 + 8, r >> 1); }
          if (r == 1) {
            float* kvp = prm.sc->kv[epoch & 1][layer][j];
            mbar_wait(bar_kvdone, layer);
            if (lane == 0) {
              bulk_reduce_f32(kvp, sbase + OFF_STG, 16384);
              bulk_reduce_f32(kvp, sbase + OFF_STG + 16384, 16384);
              asm volatile("cp.async.bulk.commit_group;\ncp.async.bulk.wait_group 0;" ::: "memory");
              fence_gpu();
              red_add_u32(&prm.sc->kvcnt[layer][j][0], 1);
              mbar_expect_tx(bar_kvready, 16896);
            }
            __syncwarp();
          }
          poll_eq(&prm.sc->cscnt[r ? 7 + r : j][0], epoch * (r ? 48 : 32));
          {
            const int q0 = r > 2 ? 4 * r - 8 : 0, nq = (0x64424 >> (4 * r)) & 15;
            const uint32_t cb = full + 224 + 56, tmp = sbase + OFF_STG + 24576;
            fence_async_global();
            if (lane == 0) mbar_expect_tx(cb, nq * 256);
            __syncwarp();
            if (lane < nq) bulk_load(tmp + lane * 256, &prm.sc->cs[epoch & 1][(r == 0 ? 1024 + 128 * j : r == 1 ? 128 * j : 3072 + 448 * j + 32 * q0)
                                                                            + (lane & 1) * (r == 0 ? 1024 : r == 1 ? 64 : F_) + (lane >> 1) * 64], 256, cb);
            mbar_wait(cb, 1 ^ (rr & 1));
            const uint32_t ad = sbase + (r == 0 ? OFF_CSKV : r == 1 ? OFF_CSQ : OFF_CSGU) + q0 * 1024;
#pragma unroll 2
            for (int q = lane; q < 64 * nq; q += 32) {
              uint32_t c1, c2, c3;
              split3(__uint_as_float(lds_u32(tmp + q * 4)), c1, c2, c3);
              sts_v4(ad + q * 16, make_uint4(c2 | (c1 >> 16), c3 | (c1 >> 16), c1 | (c2 >> 16), 0));
            }
          }
          fence_async_smem();
          __syncwarp();
          if (lane == 0) mbar_arrive(bar_cs + 8 * r);
          if (lnr) {
            poll_eq(&prm.sc->flag[layer][r ? 1 : 3][m][8 + (lane & 7)], epoch);
            __syncwarp();
            const uint32_t lb = full + 224 + 48;
            if (lane == 0) {
              fence_async_global();
              mbar_expect_tx(lb, 8192);
              bulk_load(sbase + OFF_STG + 16384, prm.sc->stats[layer * 2 + (r >> 1)][m * 128], 8192, lb);
            }
            mbar_wait(lb, 1 ^ (r >> 1));
#pragma unroll 1
            for (int q = 0; q < 4; q++) {
              float4 t0, t1, t2, t3;
              const uint32_t sp = sbase + OFF_STG + 16384 + (q * 32 + lane) * 64;
              lds_v4((uint32_t*)&t0, sp + ((lane << 3) & 48)); lds_v4((uint32_t*)&t1, sp + (((lane << 3) + 16) & 48));
              lds_v4((uint32_t*)&t2, sp + (((lane << 3) + 32) & 48)); lds_v4((uint32_t*)&t3, sp + (((lane << 3) + 48) & 48));
              const float mean = ((t0.x + t0.z) + (t1.x + t1.z) + (t2.x + t2.z) + (t3.x + t3.z)) * 0.125f;
              auto sq = [&](float v) { return (v - mean) * (v - mean); };
              const float m2 = (t0.y + t0.w) + (t1.y + t1.w) + (t2.y + t2.w) + (t3.y + t3.w)
                             + 128.f * (sq(t0.x) + sq(t0.z) + sq(t1.x) + sq(t1.z) + sq(t2.x) + sq(t2.z) + sq(t3.x) + sq(t3.z));
              uint32_t a1, a2, a3, r1, r2, r3;
              split3(-0.5f * mean, a1, a2, a3);
              split3(rsqrtf(m2 * (1.f / 1024.f) + 1e-5f), r1, r2, r3);
              sts_v4(sbase + OFF_LN + (q * 32 + lane) * 16, make_uint4(a1 | (a1 >> 16), a1 | (a2 >> 16), a3 | (a2 >> 16), r1 | (r2 >> 16)));
            }
            fence_async_smem();
            __syncwarp();
            if (lane == 0) mbar_arrive(bar_ln);
          }
          if (r == 1) {
            float* kvp = prm.sc->kv[epoch & 1][layer][j];
            poll_eq(&prm.sc->kvcnt[layer][j][0], epoch * 16);
            fence_async_global();
            if (lane < 8) bulk_load(sbase + OFF_STG + (lane & 3) * 5120 + (lane >> 2) * 4096, kvp + (lane < 4 ? lane * 1024 : 4096 + (lane & 3) * 32), lane < 4 ? 4096 : 128, bar_kvready);
            __syncwarp();
          }
        }
      }
    }
  }
  __syncwarp();
  if (helper || warp < 4) asm volatile("barrier.cluster.arrive.relaxed.aligned;" ::: "memory");
  cluster_wait();
}

typedef CUresult (*EncodeTiledFn)(CUtensorMap*, CUtensorMapDataType, cuuint32_t, void*, const cuuint64_t*, const cuuint64_t*, const cuuint32_t*, const cuuint32_t*,
                                  CUtensorMapInterleave, CUtensorMapSwizzle, CUtensorMapL2promotion, CUtensorMapFloatOOBfill);

void make_wmap(EncodeTiledFn enc, CUtensorMap* m, const void* ptr, uint64_t rows, uint64_t cols, bool perm) {
  uint64_t rs = cols * 2;
  cuuint64_t gd[5] = {cols, 2, 4, 4, rows / 32};
  cuuint64_t gs[4] = {rs, (perm ? 8 : 2) * rs, (perm ? 2 : 8) * rs, 32 * rs};
  cuuint32_t bd[5] = {64, 2, 4, 4, 2}, es[5] = {1, 1, 1, 1, 1};
  enc(m, CU_TENSOR_MAP_DATA_TYPE_BFLOAT16, 5, (void*)ptr, gd, gs, bd, es, CU_TENSOR_MAP_INTERLEAVE_NONE, CU_TENSOR_MAP_SWIZZLE_128B,
      CU_TENSOR_MAP_L2_PROMOTION_L2_256B, CU_TENSOR_MAP_FLOAT_OOB_FILL_NONE);
}

void make_2d(EncodeTiledFn enc, CUtensorMap* m, const void* ptr, uint64_t rows, uint64_t cols, uint32_t box_rows) {
  cuuint64_t gd[2] = {cols, rows}, gs[1] = {cols * 2}; cuuint32_t bd[2] = {64, box_rows}, es[2] = {1, 1};
  enc(m, CU_TENSOR_MAP_DATA_TYPE_BFLOAT16, 2, (void*)ptr, gd, gs, bd, es, CU_TENSOR_MAP_INTERLEAVE_NONE, CU_TENSOR_MAP_SWIZZLE_128B,
      CU_TENSOR_MAP_L2_PROMOTION_L2_256B, CU_TENSOR_MAP_FLOAT_OOB_FILL_NONE);
}

}

extern "C" void kernel_launch(void* const* d_in, const int* in_sizes, int n_in, void* d_out, int out_size) {
  const __nv_bfloat16* x = (const __nv_bfloat16*)d_in[0];
  const __nv_bfloat16* wqkv = (const __nv_bfloat16*)d_in[1];
  const __nv_bfloat16* wo = (const __nv_bfloat16*)d_in[2];
  const __nv_bfloat16* wg = (const __nv_bfloat16*)d_in[4];
  const __nv_bfloat16* wu = (const __nv_bfloat16*)d_in[5];
  const __nv_bfloat16* wd = (const __nv_bfloat16*)d_in[6];

  void* fn = nullptr; cudaDriverEntryPointQueryResult qr;
  cudaGetDriverEntryPoint("cuTensorMapEncodeTiled", &fn, cudaEnableDefault, &qr);
  EncodeTiledFn enc = (EncodeTiledFn)fn;
  Params prm;
  make_2d(enc, &prm.x, x, S_, D_, 128);
  make_wmap(enc, &prm.wqkv_n, wqkv, D_, 3 * D_, false);
  make_wmap(enc, &prm.wqkv_p, wqkv, D_, 3 * D_, true);
  make_wmap(enc, &prm.wo_p, wo, D_, D_, true);
  make_wmap(enc, &prm.wg_p, wg, D_, F_, true);
  make_wmap(enc, &prm.wu_p, wu, D_, F_, true);
  make_wmap(enc, &prm.wd_p, wd, F_, D_, true);
  prm.xin = x; prm.out = (__nv_bfloat16*)d_out;
  cudaGetSymbolAddress((void**)&prm.sc, g_scratch);

  cudaFuncSetAttribute(fused_kernel, cudaFuncAttributeMaxDynamicSharedMemorySize, SMEM_BYTES);
  cudaLaunchConfig_t cfg = {};
  cfg.gridDim = dim3(132); cfg.blockDim = dim3(384); cfg.dynamicSmemBytes = SMEM_BYTES; cfg.stream = cudaStreamPerThread;
  cudaLaunchAttribute at[1];
  at[0].id = cudaLaunchAttributeClusterDimension; at[0].val.clusterDim.x = 2; at[0].val.clusterDim.y = 1; at[0].val.clusterDim.z = 1;
  cfg.attrs = at; cfg.numAttrs = 1;
  cudaLaunchKernelEx(&cfg, fused_kernel, prm);
}
```

```cpp
#include <cuda_runtime.h>
#include <cuda_bf16.h>
#include <cuda.h>
#include <stdint.h>

namespace {

constexpr int S_ = 2048, D_ = 1024, F_ = 3584;
constexpr int NSLOT = 12;
constexpr uint32_t SLOT = 16384;
constexpr uint32_t OFF_STG = NSLOT * SLOT;
constexpr uint32_t OFF_LN = OFF_STG + 32768;
constexpr uint32_t OFF_ONES = OFF_LN + 2048;
constexpr uint32_t OFF_BAR = OFF_ONES + 256;
constexpr uint32_t SMEM_BYTES = OFF_BAR + 512;
constexpr uint32_t OFF_CSKV = OFF_STG + 28672, OFF_CSQ = OFF_STG + 20480, OFF_CSGU = OFF_STG;

struct Scratch {
  uint8_t o[16 * 16 * SLOT], x1[16 * 16 * SLOT], x2[16 * 16 * SLOT], h[16 * 56 * SLOT];
  float2 stats[4][S_][8];
  float cs[2][3072 + 2 * F_];
  float kv[2][2][8][4224];
  uint32_t flag[2][4][16][32];
  uint32_t kvcnt[2][8][32];
  uint32_t cscnt[12][32];
  uint32_t epoch;
};
__device__ __align__(1024) Scratch g_scratch;

struct Params {
  CUtensorMap x, wqkv_n, wqkv_p, wo_p, wg_p, wu_p, wd_p;
  const __nv_bfloat16* xin;
  __nv_bfloat16* out;
  Scratch* sc;
  int role[66];
};

__device__ __forceinline__ uint32_t smem_u32(const void* p) { return (uint32_t)__cvta_generic_to_shared(p); }
__device__ __forceinline__ void mbar_init(uint32_t bar, uint32_t count) { asm volatile("mbarrier.init.shared::cta.b64 [%0], %1;" :: "r"(bar), "r"(count) : "memory"); }
__device__ __forceinline__ void mbar_expect_tx(uint32_t bar, uint32_t bytes) { asm volatile("mbarrier.arrive.expect_tx.shared::cta.b64 _, [%0], %1;" :: "r"(bar), "r"(bytes) : "memory"); }
__device__ __forceinline__ void mbar_arrive(uint32_t bar) { asm volatile("mbarrier.arrive.shared::cta.b64 _, [%0];" :: "r"(bar) : "memory"); }
__device__ __forceinline__ void mbar_arrive_cluster(uint32_t bar, uint32_t cta) {
  asm volatile("{\n.reg .b32 ra;\nmapa.shared::cluster.u32 ra, %0, %1;\nmbarrier.arrive.shared::cluster.b64 _, [ra];\n}\n" :: "r"(bar), "r"(cta) : "memory");
}
__device__ __forceinline__ void mbar_arrive_if(uint32_t bar, bool pred) {
  asm volatile("{\n.reg .pred p;\nsetp.ne.b32 p, %1, 0;\n@p mbarrier.arrive.shared::cta.b64 _, [%0];\n}\n" :: "r"(bar), "r"((uint32_t)pred) : "memory");
}
__device__ __forceinline__ void mbar_arrive_remote_if(uint32_t cluster_addr, bool pred) {
  asm volatile("{\n.reg .pred p;\nsetp.ne.b32 p, %1, 0;\n@p mbarrier.arrive.shared::cluster.b64 _, [%0];\n}\n" :: "r"(cluster_addr), "r"((uint32_t)pred) : "memory");
}
__device__ __forceinline__ uint32_t mapa(uint32_t addr, uint32_t cta) { uint32_t r; asm("mapa.shared::cluster.u32 %0, %1, %2;" : "=r"(r) : "r"(addr), "r"(cta)); return r; }
__device__ __forceinline__ void st_f2_if(float2* ptr, float a, float b, bool pred) {
  asm volatile("{\n.reg .pred p;\nsetp.ne.b32 p, %3, 0;\n@p st.global.v2.f32 [%0], {%1, %2};\n}\n" :: "l"(ptr), "f"(a), "f"(b), "r"((uint32_t)pred) : "memory");
}
__device__ __forceinline__ void stg_v4_if(void* ptr, const uint32_t* v, bool pred) {
  asm volatile("{\n.reg .pred p;\nsetp.ne.b32 p, %5, 0;\n@p st.global.v4.u32 [%0], {%1, %2, %3, %4};\n}\n" :: "l"(ptr), "r"(v[0]), "r"(v[1]), "r"(v[2]), "r"(v[3]), "r"((uint32_t)pred) : "memory");
}
__device__ __forceinline__ void red_add_f32_if(float* ptr, float v, bool pred) {
  asm volatile("{\n.reg .pred p;\nsetp.ne.b32 p, %2, 0;\n@p red.relaxed.gpu.global.add.f32 [%0], %1;\n}\n" :: "l"(ptr), "f"(v), "r"((uint32_t)pred) : "memory");
}
__device__ __forceinline__ void mbar_wait(uint32_t bar, uint32_t parity) {
  asm volatile("{\n.reg .pred p;\n.reg .b32 n;\nmov.b32 n, 0;\nWAIT_LOOP:\n"
               "mbarrier.try_wait.parity.shared::cta.b64 p, [%0], %1;\n@p bra WAIT_DONE;\n"
               "add.u32 n, n, 1;\nsetp.lt.u32 p, n, 1048576;\n@p bra WAIT_LOOP;\ntrap;\nWAIT_DONE:\n}\n" :: "r"(bar), "r"(parity) : "memory");
}
__device__ __forceinline__ uint32_t ld_acquire(const uint32_t* p) { uint32_t v; asm volatile("ld.acquire.gpu.global.u32 %0, [%1];" : "=r"(v) : "l"(p) : "memory"); return v; }
__device__ __forceinline__ uint32_t ld_relaxed(const uint32_t* p) { uint32_t v; asm volatile("ld.relaxed.gpu.global.u32 %0, [%1];" : "=r"(v) : "l"(p) : "memory"); return v; }
#define POLL ld_acquire
__device__ __forceinline__ void poll_eq(const uint32_t* p, uint32_t want) {
  uint32_t n = 0;
  while (ld_acquire(p) != want) { if (++n > (1u << 20)) __trap(); }
}
__device__ __forceinline__ void tma_2d(uint32_t dst, const CUtensorMap* m, uint32_t bar, int c0, int c1) {
  asm volatile("cp.async.bulk.tensor.2d.shared::cluster.global.mbarrier::complete_tx::bytes [%0], [%1, {%3, %4}], [%2];"
    :: "r"(dst), "l"((uint64_t)m), "r"(bar), "r"(c0), "r"(c1) : "memory");
}
__device__ __forceinline__ void tma_5d_mc(uint32_t dst, const CUtensorMap* m, uint32_t bar, int c0, int c4) {
  asm volatile("cp.async.bulk.tensor.5d.shared::cluster.global.mbarrier::complete_tx::bytes.multicast::cluster [%0], [%1, {%3, %5, %5, %5, %4}], [%2], %6;"
    :: "r"(dst), "l"((uint64_t)m), "r"(bar), "r"(c0), "r"(c4), "r"(0), "h"((uint16_t)3) : "memory");
}
__device__ __forceinline__ void tma_5d(uint32_t dst, const CUtensorMap* m, uint32_t bar, int c0, int c4) {
  asm volatile("cp.async.bulk.tensor.5d.shared::cluster.global.mbarrier::complete_tx::bytes [%0], [%1, {%3, %5, %5, %5, %4}], [%2];"
    :: "r"(dst), "l"((uint64_t)m), "r"(bar), "r"(c0), "r"(c4), "r"(0) : "memory");
}
__device__ __forceinline__ void tma_5d_prefetch(const CUtensorMap* m, int c0, int c4) {
  asm volatile("cp.async.bulk.prefetch.tensor.5d.L2.global.tile [%0, {%1, %3, %3, %3, %2}];" :: "l"((uint64_t)m), "r"(c0), "r"(c4), "r"(0) : "memory");
}
__device__ __forceinline__ void bulk_load(uint32_t dst, const void* src, uint32_t bytes, uint32_t bar) {
  asm volatile("cp.async.bulk.shared::cluster.global.mbarrier::complete_tx::bytes [%0], [%1], %2, [%3];"
    :: "r"(dst), "l"((uint64_t)src), "r"(bytes), "r"(bar) : "memory");
}
__device__ __forceinline__ void bulk_store(void* dst, uint32_t src, uint32_t bytes) {
  asm volatile("cp.async.bulk.global.shared::cta.bulk_group [%0], [%1], %2;" :: "l"((uint64_t)dst), "r"(src), "r"(bytes) : "memory");
}
#define SKW 1
#define SKN 2
#define KFENCE wgmma_fence()
#define HS 1
#define RSK 2
#define PFSLEEP 500
#define PFTAB 0x988654431ull
#define OWN_FENCE
__device__ __forceinline__ void bulk_reduce_f32(void* dst, uint32_t src, uint32_t bytes) {
  asm volatile("cp.reduce.async.bulk.global.shared::cta.bulk_group.add.f32 [%0], [%1], %2;" :: "l"((uint64_t)dst), "r"(src), "r"(bytes) : "memory");
}
__device__ __forceinline__ void wgmma_fence() { asm volatile("wgmma.fence.sync.aligned;" ::: "memory"); }
__device__ __forceinline__ void wgmma_commit() { asm volatile("wgmma.commit_group.sync.aligned;" ::: "memory"); }
template<int N> __device__ __forceinline__ void wgmma_wait() { asm volatile("wgmma.wait_group.sync.aligned %0;" :: "n"(N) : "memory"); }
__device__ __forceinline__ void cluster_sync() { asm volatile("barrier.cluster.arrive.release.aligned;\nbarrier.cluster.wait.acquire.aligned;" ::: "memory"); }
__device__ __forceinline__ void cluster_wait() { asm volatile("barrier.cluster.wait.acquire.aligned;" ::: "memory"); }
__device__ __forceinline__ void fence_async_smem() { asm volatile("fence.proxy.async.shared::cta;" ::: "memory"); }
__device__ __forceinline__ void fence_async_global() { asm volatile("fence.proxy.async.global;" ::: "memory"); }
__device__ __forceinline__ void fence_gpu() { asm volatile("fence.acq_rel.gpu;" ::: "memory"); }
__device__ __forceinline__ void wg_bar(int id) { asm volatile("bar.sync %0, 128;" :: "r"(id) : "memory"); }
__device__ __forceinline__ void st_relaxed(uint32_t* p, uint32_t v) { asm volatile("st.relaxed.gpu.global.u32 [%0], %1;" :: "l"(p), "r"(v) : "memory"); }
__device__ __forceinline__ void red_add_u32(uint32_t* p, uint32_t v) { asm volatile("red.relaxed.gpu.global.add.u32 [%0], %1;" :: "l"(p), "r"(v) : "memory"); }
__device__ __forceinline__ void red_add_f32(float* p, float v) { asm volatile("red.relaxed.gpu.global.add.f32 [%0], %1;" :: "l"(p), "f"(v) : "memory"); }
__device__ __forceinline__ void red_add_v4(float* p, float a, float b, float c, float d) {
  asm volatile("red.relaxed.gpu.global.add.v4.f32 [%0], {%1, %2, %3, %4};" :: "l"(p), "f"(a), "f"(b), "f"(c), "f"(d) : "memory");
}
__device__ __forceinline__ void stmatrix_x4(uint32_t addr, uint32_t r0, uint32_t r1, uint32_t r2, uint32_t r3) {
  asm volatile("stmatrix.sync.aligned.m8n8.x4.shared.b16 [%0], {%1, %2, %3, %4};" :: "r"(addr), "r"(r0), "r"(r1), "r"(r2), "r"(r3) : "memory");
}
__device__ __forceinline__ float2 lds_f2(uint32_t addr) { float2 v; asm volatile("ld.shared.v2.f32 {%0, %1}, [%2];" : "=f"(v.x), "=f"(v.y) : "r"(addr)); return v; }
__device__ __forceinline__ uint32_t lds_u32(uint32_t addr) { uint32_t v; asm volatile("ld.shared.u32 %0, [%1];" : "=r"(v) : "r"(addr) : "memory"); return v; }
__device__ __forceinline__ void sts_u32(uint32_t addr, uint32_t v) { asm volatile("st.shared.u32 [%0], %1;" :: "r"(addr), "r"(v) : "memory"); }
__device__ __forceinline__ void sts_v4(uint32_t addr, uint4 v) { asm volatile("st.shared.v4.u32 [%0], {%1, %2, %3, %4};" :: "r"(addr), "r"(v.x), "r"(v.y), "r"(v.z), "r"(v.w) : "memory"); }
__device__ __forceinline__ uint32_t pack_bf16(float lo, float hi) { uint32_t r; asm("cvt.rn.bf16x2.f32 %0, %1, %2;" : "=r"(r) : "f"(hi), "f"(lo)); return r; }
__device__ __forceinline__ float bf_lo(uint32_t v) { return __uint_as_float(v << 16); }
__device__ __forceinline__ float bf_hi(uint32_t v) { return __uint_as_float(v & 0xffff0000u); }
__device__ __forceinline__ float ex2f(float x) { float r; asm("ex2.approx.ftz.f32 %0, %1;" : "=f"(r) : "f"(x)); return r; }
__device__ __forceinline__ float rcpf(float x) { float r; asm("rcp.approx.ftz.f32 %0, %1;" : "=f"(r) : "f"(x)); return r; }
__device__ __forceinline__ float phif(float t) { return (t > 0.f ? t + 1.f : ex2f(t * 1.4426950408889634f)) + 1e-6f; }
__device__ __forceinline__ uint32_t make_desc(uint32_t addr, uint32_t lbo) { return ((addr & 0x3FFFF) >> 4) | ((lbo >> 4) << 16); }
__device__ __forceinline__ bool mbar_test(uint32_t bar, uint32_t parity) {
  uint32_t ok;
  asm volatile("{\n.reg .pred p;\nmbarrier.test_wait.parity.shared::cta.b64 p, [%1], %2;\nselp.u32 %0, 1, 0, p;\n}\n" : "=r"(ok) : "r"(bar), "r"(parity) : "memory");
  return ok;
}
__device__ __forceinline__ int lane_id() { int r; asm volatile("mov.u32 %0, %%laneid;" : "=r"(r)); return r; }
#define load_epoch() (__ldcg(&prm.sc->epoch) + 1)
__device__ __forceinline__ bool elect_one() {
  uint32_t r;
  asm volatile("{\n.reg .pred p;\nelect.sync _|p, 0xffffffff;\nselp.u32 %0, 1, 0, p;\n}\n" : "=r"(r));
  return r;
}
__device__ __forceinline__ uint32_t hadd2(uint32_t a, uint32_t b) { uint32_t r; asm("add.rn.bf16x2 %0, %1, %2;" : "=r"(r) : "r"(a), "r"(b)); return r; }
__device__ __forceinline__ uint32_t hmul2(uint32_t a, uint32_t b) { uint32_t r; asm("mul.rn.bf16x2 %0, %1, %2;" : "=r"(r) : "r"(a), "r"(b)); return r; }
__device__ __forceinline__ unsigned long long gtime() { unsigned long long t; asm volatile("mov.u64 %0, %%globaltimer;" : "=l"(t)); return t; }

template<bool INIT> __device__ __forceinline__ void wgmma_n256_ss(float* d, uint32_t da, uint32_t db) {
  if constexpr (INIT) {
  asm volatile("{\n.reg .pred p;\n.reg .b64 da, db;\nsetp.ne.b32 p, 0, 0;\nmov.b64 da, {%128, 0x40000040};\nmov.b64 db, {%129, 0x40000040};\nwgmma.mma_async.sync.aligned.m64n256k16.f32.bf16.bf16 {%0, %1, %2, %3, %4, %5, %6, %7, %8, %9, %10, %11, %12, %13, %14, %15, %16, %17, %18, %19, %20, %21, %22, %23, %24, %25, %26, %27, %28, %29, %30, %31, %32, %33, %34, %35, %36, %37, %38, %39, %40, %41, %42, %43, %44, %45, %46, %47, %48, %49, %50, %51, %52, %53, %54, %55, %56, %57, %58, %59, %60, %61, %62, %63, %64, %65, %66, %67, %68, %69, %70, %71, %72, %73, %74, %75, %76, %77, %78, %79, %80, %81, %82, %83, %84, %85, %86, %87, %88, %89, %90, %91, %92, %93, %94, %95, %96, %97, %98, %99, %100, %101, %102, %103, %104, %105, %106, %107, %108, %109, %110, %111, %112, %113, %114, %115, %116, %117, %118, %119, %120, %121, %122, %123, %124, %125, %126, %127}, da, db, p, 1, 1, 0, 1;\n}\n"
    : "=f"(d[0]), "=f"(d[1]), "=f"(d[2]), "=f"(d[3]), "=f"(d[4]), "=f"(d[5]), "=f"(d[6]), "=f"(d[7]), "=f"(d[8]), "=f"(d[9]), "=f"(d[10]), "=f"(d[11]), "=f"(d[12]), "=f"(d[13]), "=f"(d[14]), "=f"(d[15]), "=f"(d[16]), "=f"(d[17]), "=f"(d[18]), "=f"(d[19]), "=f"(d[20]), "=f"(d[21]), "=f"(d[22]), "=f"(d[23]), "=f"(d[24]), "=f"(d[25]), "=f"(d[26]), "=f"(d[27]), "=f"(d[28]), "=f"(d[29]), "=f"(d[30]), "=f"(d[31]), "=f"(d[32]), "=f"(d[33]), "=f"(d[34]), "=f"(d[35]), "=f"(d[36]), "=f"(d[37]), "=f"(d[38]), "=f"(d[39]), "=f"(d[40]), "=f"(d[41]), "=f"(d[42]), "=f"(d[43]), "=f"(d[44]), "=f"(d[45]), "=f"(d[46]), "=f"(d[47]), "=f"(d[48]), "=f"(d[49]), "=f"(d[50]), "=f"(d[51]), "=f"(d[52]), "=f"(d[53]), "=f"(d[54]), "=f"(d[55]), "=f"(d[56]), "=f"(d[57]), "=f"(d[58]), "=f"(d[59]), "=f"(d[60]), "=f"(d[61]), "=f"(d[62]), "=f"(d[63]), "=f"(d[64]), "=f"(d[65]), "=f"(d[66]), "=f"(d[67]), "=f"(d[68]), "=f"(d[69]), "=f"(d[70]), "=f"(d[71]), "=f"(d[72]), "=f"(d[73]), "=f"(d[74]), "=f"(d[75]), "=f"(d[76]), "=f"(d[77]), "=f"(d[78]), "=f"(d[79]), "=f"(d[80]), "=f"(d[81]), "=f"(d[82]), "=f"(d[83]), "=f"(d[84]), "=f"(d[85]), "=f"(d[86]), "=f"(d[87]), "=f"(d[88]), "=f"(d[89]), "=f"(d[90]), "=f"(d[91]), "=f"(d[92]), "=f"(d[93]), "=f"(d[94]), "=f"(d[95]), "=f"(d[96]), "=f"(d[97]), "=f"(d[98]), "=f"(d[99]), "=f"(d[100]), "=f"(d[101]), "=f"(d[102]), "=f"(d[103]), "=f"(d[104]), "=f"(d[105]), "=f"(d[106]), "=f"(d[107]), "=f"(d[108]), "=f"(d[109]), "=f"(d[110]), "=f"(d[111]), "=f"(d[112]), "=f"(d[113]), "=f"(d[114]), "=f"(d[115]), "=f"(d[116]), "=f"(d[117]), "=f"(d[118]), "=f"(d[119]), "=f"(d[120]), "=f"(d[121]), "=f"(d[122]), "=f"(d[123]), "=f"(d[124]), "=f"(d[125]), "=f"(d[126]), "=f"(d[127])
    : "r"(da), "r"(db));
  } else {
  asm volatile("{\n.reg .pred p;\n.reg .b64 da, db;\nsetp.ne.b32 p, 1, 0;\nmov.b64 da, {%128, 0x40000040};\nmov.b64 db, {%129, 0x40000040};\nwgmma.mma_async.sync.aligned.m64n256k16.f32.bf16.bf16 {%0, %1, %2, %3, %4, %5, %6, %7, %8, %9, %10, %11, %12, %13, %14, %15, %16, %17, %18, %19, %20, %21, %22, %23, %24, %25, %26, %27, %28, %29, %30, %31, %32, %33, %34, %35, %36, %37, %38, %39, %40, %41, %42, %43, %44, %45, %46, %47, %48, %49, %50, %51, %52, %53, %54, %55, %56, %57, %58, %59, %60, %61, %62, %63, %64, %65, %66, %67, %68, %69, %70, %71, %72, %73, %74, %75, %76, %77, %78, %79, %80, %81, %82, %83, %84, %85, %86, %87, %88, %89, %90, %91, %92, %93, %94, %95, %96, %97, %98, %99, %100, %101, %102, %103, %104, %105, %106, %107, %108, %109, %110, %111, %112, %113, %114, %115, %116, %117, %118, %119, %120, %121, %122, %123, %124, %125, %126, %127}, da, db, p, 1, 1, 0, 1;\n}\n"
    : "+f"(d[0]), "+f"(d[1]), "+f"(d[2]), "+f"(d[3]), "+f"(d[4]), "+f"(d[5]), "+f"(d[6]), "+f"(d[7]), "+f"(d[8]), "+f"(d[9]), "+f"(d[10]), "+f"(d[11]), "+f"(d[12]), "+f"(d[13]), "+f"(d[14]), "+f"(d[15]), "+f"(d[16]), "+f"(d[17]), "+f"(d[18]), "+f"(d[19]), "+f"(d[20]), "+f"(d[21]), "+f"(d[22]), "+f"(d[23]), "+f"(d[24]), "+f"(d[25]), "+f"(d[26]), "+f"(d[27]), "+f"(d[28]), "+f"(d[29]), "+f"(d[30]), "+f"(d[31]), "+f"(d[32]), "+f"(d[33]), "+f"(d[34]), "+f"(d[35]), "+f"(d[36]), "+f"(d[37]), "+f"(d[38]), "+f"(d[39]), "+f"(d[40]), "+f"(d[41]), "+f"(d[42]), "+f"(d[43]), "+f"(d[44]), "+f"(d[45]), "+f"(d[46]), "+f"(d[47]), "+f"(d[48]), "+f"(d[49]), "+f"(d[50]), "+f"(d[51]), "+f"(d[52]), "+f"(d[53]), "+f"(d[54]), "+f"(d[55]), "+f"(d[56]), "+f"(d[57]), "+f"(d[58]), "+f"(d[59]), "+f"(d[60]), "+f"(d[61]), "+f"(d[62]), "+f"(d[63]), "+f"(d[64]), "+f"(d[65]), "+f"(d[66]), "+f"(d[67]), "+f"(d[68]), "+f"(d[69]), "+f"(d[70]), "+f"(d[71]), "+f"(d[72]), "+f"(d[73]), "+f"(d[74]), "+f"(d[75]), "+f"(d[76]), "+f"(d[77]), "+f"(d[78]), "+f"(d[79]), "+f"(d[80]), "+f"(d[81]), "+f"(d[82]), "+f"(d[83]), "+f"(d[84]), "+f"(d[85]), "+f"(d[86]), "+f"(d[87]), "+f"(d[88]), "+f"(d[89]), "+f"(d[90]), "+f"(d[91]), "+f"(d[92]), "+f"(d[93]), "+f"(d[94]), "+f"(d[95]), "+f"(d[96]), "+f"(d[97]), "+f"(d[98]), "+f"(d[99]), "+f"(d[100]), "+f"(d[101]), "+f"(d[102]), "+f"(d[103]), "+f"(d[104]), "+f"(d[105]), "+f"(d[106]), "+f"(d[107]), "+f"(d[108]), "+f"(d[109]), "+f"(d[110]), "+f"(d[111]), "+f"(d[112]), "+f"(d[113]), "+f"(d[114]), "+f"(d[115]), "+f"(d[116]), "+f"(d[117]), "+f"(d[118]), "+f"(d[119]), "+f"(d[120]), "+f"(d[121]), "+f"(d[122]), "+f"(d[123]), "+f"(d[124]), "+f"(d[125]), "+f"(d[126]), "+f"(d[127])
    : "r"(da), "r"(db));
  }
}
template<bool INIT> __device__ __forceinline__ void wgmma_n128_ss(float* d, uint32_t da, uint32_t db) {
  if constexpr (INIT) {
  asm volatile("{\n.reg .pred p;\n.reg .b64 da, db;\nsetp.ne.b32 p, 0, 0;\nmov.b64 da, {%64, 0x40000040};\nmov.b64 db, {%65, 0x40000040};\nwgmma.mma_async.sync.aligned.m64n128k16.f32.bf16.bf16 {%0, %1, %2, %3, %4, %5, %6, %7, %8, %9, %10, %11, %12, %13, %14, %15, %16, %17, %18, %19, %20, %21, %22, %23, %24, %25, %26, %27, %28, %29, %30, %31, %32, %33, %34, %35, %36, %37, %38, %39, %40, %41, %42, %43, %44, %45, %46, %47, %48, %49, %50, %51, %52, %53, %54, %55, %56, %57, %58, %59, %60, %61, %62, %63}, da, db, p, 1, 1, 0, 1;\n}\n"
    : "=f"(d[0]), "=f"(d[1]), "=f"(d[2]), "=f"(d[3]), "=f"(d[4]), "=f"(d[5]), "=f"(d[6]), "=f"(d[7]), "=f"(d[8]), "=f"(d[9]), "=f"(d[10]), "=f"(d[11]), "=f"(d[12]), "=f"(d[13]), "=f"(d[14]), "=f"(d[15]), "=f"(d[16]), "=f"(d[17]), "=f"(d[18]), "=f"(d[19]), "=f"(d[20]), "=f"(d[21]), "=f"(d[22]), "=f"(d[23]), "=f"(d[24]), "=f"(d[25]), "=f"(d[26]), "=f"(d[27]), "=f"(d[28]), "=f"(d[29]), "=f"(d[30]), "=f"(d[31]), "=f"(d[32]), "=f"(d[33]), "=f"(d[34]), "=f"(d[35]), "=f"(d[36]), "=f"(d[37]), "=f"(d[38]), "=f"(d[39]), "=f"(d[40]), "=f"(d[41]), "=f"(d[42]), "=f"(d[43]), "=f"(d[44]), "=f"(d[45]), "=f"(d[46]), "=f"(d[47]), "=f"(d[48]), "=f"(d[49]), "=f"(d[50]), "=f"(d[51]), "=f"(d[52]), "=f"(d[53]), "=f"(d[54]), "=f"(d[55]), "=f"(d[56]), "=f"(d[57]), "=f"(d[58]), "=f"(d[59]), "=f"(d[60]), "=f"(d[61]), "=f"(d[62]), "=f"(d[63])
    : "r"(da), "r"(db));
  } else {
  asm volatile("{\n.reg .pred p;\n.reg .b64 da, db;\nsetp.ne.b32 p, 1, 0;\nmov.b64 da, {%64, 0x40000040};\nmov.b64 db, {%65, 0x40000040};\nwgmma.mma_async.sync.aligned.m64n128k16.f32.bf16.bf16 {%0, %1, %2, %3, %4, %5, %6, %7, %8, %9, %10, %11, %12, %13, %14, %15, %16, %17, %18, %19, %20, %21, %22, %23, %24, %25, %26, %27, %28, %29, %30, %31, %32, %33, %34, %35, %36, %37, %38, %39, %40, %41, %42, %43, %44, %45, %46, %47, %48, %49, %50, %51, %52, %53, %54, %55, %56, %57, %58, %59, %60, %61, %62, %63}, da, db, p, 1, 1, 0, 1;\n}\n"
    : "+f"(d[0]), "+f"(d[1]), "+f"(d[2]), "+f"(d[3]), "+f"(d[4]), "+f"(d[5]), "+f"(d[6]), "+f"(d[7]), "+f"(d[8]), "+f"(d[9]), "+f"(d[10]), "+f"(d[11]), "+f"(d[12]), "+f"(d[13]), "+f"(d[14]), "+f"(d[15]), "+f"(d[16]), "+f"(d[17]), "+f"(d[18]), "+f"(d[19]), "+f"(d[20]), "+f"(d[21]), "+f"(d[22]), "+f"(d[23]), "+f"(d[24]), "+f"(d[25]), "+f"(d[26]), "+f"(d[27]), "+f"(d[28]), "+f"(d[29]), "+f"(d[30]), "+f"(d[31]), "+f"(d[32]), "+f"(d[33]), "+f"(d[34]), "+f"(d[35]), "+f"(d[36]), "+f"(d[37]), "+f"(d[38]), "+f"(d[39]), "+f"(d[40]), "+f"(d[41]), "+f"(d[42]), "+f"(d[43]), "+f"(d[44]), "+f"(d[45]), "+f"(d[46]), "+f"(d[47]), "+f"(d[48]), "+f"(d[49]), "+f"(d[50]), "+f"(d[51]), "+f"(d[52]), "+f"(d[53]), "+f"(d[54]), "+f"(d[55]), "+f"(d[56]), "+f"(d[57]), "+f"(d[58]), "+f"(d[59]), "+f"(d[60]), "+f"(d[61]), "+f"(d[62]), "+f"(d[63])
    : "r"(da), "r"(db));
  }
}
template<bool INIT> __device__ __forceinline__ void wgmma_n256_nn(float* d, uint32_t da, uint32_t db) {
  if constexpr (INIT) {
  asm volatile("{\n.reg .pred p;\n.reg .b64 da, db;\nsetp.ne.b32 p, 0, 0;\nmov.b64 da, {%128, 8};\nmov.b64 db, {%129, 8};\nwgmma.mma_async.sync.aligned.m64n256k16.f32.bf16.bf16 {%0, %1, %2, %3, %4, %5, %6, %7, %8, %9, %10, %11, %12, %13, %14, %15, %16, %17, %18, %19, %20, %21, %22, %23, %24, %25, %26, %27, %28, %29, %30, %31, %32, %33, %34, %35, %36, %37, %38, %39, %40, %41, %42, %43, %44, %45, %46, %47, %48, %49, %50, %51, %52, %53, %54, %55, %56, %57, %58, %59, %60, %61, %62, %63, %64, %65, %66, %67, %68, %69, %70, %71, %72, %73, %74, %75, %76, %77, %78, %79, %80, %81, %82, %83, %84, %85, %86, %87, %88, %89, %90, %91, %92, %93, %94, %95, %96, %97, %98, %99, %100, %101, %102, %103, %104, %105, %106, %107, %108, %109, %110, %111, %112, %113, %114, %115, %116, %117, %118, %119, %120, %121, %122, %123, %124, %125, %126, %127}, da, db, p, 1, 1, 0, 0;\n}\n"
    : "=f"(d[0]), "=f"(d[1]), "=f"(d[2]), "=f"(d[3]), "=f"(d[4]), "=f"(d[5]), "=f"(d[6]), "=f"(d[7]), "=f"(d[8]), "=f"(d[9]), "=f"(d[10]), "=f"(d[11]), "=f"(d[12]), "=f"(d[13]), "=f"(d[14]), "=f"(d[15]), "=f"(d[16]), "=f"(d[17]), "=f"(d[18]), "=f"(d[19]), "=f"(d[20]), "=f"(d[21]), "=f"(d[22]), "=f"(d[23]), "=f"(d[24]), "=f"(d[25]), "=f"(d[26]), "=f"(d[27]), "=f"(d[28]), "=f"(d[29]), "=f"(d[30]), "=f"(d[31]), "=f"(d[32]), "=f"(d[33]), "=f"(d[34]), "=f"(d[35]), "=f"(d[36]), "=f"(d[37]), "=f"(d[38]), "=f"(d[39]), "=f"(d[40]), "=f"(d[41]), "=f"(d[42]), "=f"(d[43]), "=f"(d[44]), "=f"(d[45]), "=f"(d[46]), "=f"(d[47]), "=f"(d[48]), "=f"(d[49]), "=f"(d[50]), "=f"(d[51]), "=f"(d[52]), "=f"(d[53]), "=f"(d[54]), "=f"(d[55]), "=f"(d[56]), "=f"(d[57]), "=f"(d[58]), "=f"(d[59]), "=f"(d[60]), "=f"(d[61]), "=f"(d[62]), "=f"(d[63]), "=f"(d[64]), "=f"(d[65]), "=f"(d[66]), "=f"(d[67]), "=f"(d[68]), "=f"(d[69]), "=f"(d[70]), "=f"(d[71]), "=f"(d[72]), "=f"(d[73]), "=f"(d[74]), "=f"(d[75]), "=f"(d[76]), "=f"(d[77]), "=f"(d[78]), "=f"(d[79]), "=f"(d[80]), "=f"(d[81]), "=f"(d[82]), "=f"(d[83]), "=f"(d[84]), "=f"(d[85]), "=f"(d[86]), "=f"(d[87]), "=f"(d[88]), "=f"(d[89]), "=f"(d[90]), "=f"(d[91]), "=f"(d[92]), "=f"(d[93]), "=f"(d[94]), "=f"(d[95]), "=f"(d[96]), "=f"(d[97]), "=f"(d[98]), "=f"(d[99]), "=f"(d[100]), "=f"(d[101]), "=f"(d[102]), "=f"(d[103]), "=f"(d[104]), "=f"(d[105]), "=f"(d[106]), "=f"(d[107]), "=f"(d[108]), "=f"(d[109]), "=f"(d[110]), "=f"(d[111]), "=f"(d[112]), "=f"(d[113]), "=f"(d[114]), "=f"(d[115]), "=f"(d[116]), "=f"(d[117]), "=f"(d[118]), "=f"(d[119]), "=f"(d[120]), "=f"(d[121]), "=f"(d[122]), "=f"(d[123]), "=f"(d[124]), "=f"(d[125]), "=f"(d[126]), "=f"(d[127])
    : "r"(da), "r"(db));
  } else {
  asm volatile("{\n.reg .pred p;\n.reg .b64 da, db;\nsetp.ne.b32 p, 1, 0;\nmov.b64 da, {%128, 8};\nmov.b64 db, {%129, 8};\nwgmma.mma_async.sync.aligned.m64n256k16.f32.bf16.bf16 {%0, %1, %2, %3, %4, %5, %6, %7, %8, %9, %10, %11, %12, %13, %14, %15, %16, %17, %18, %19, %20, %21, %22, %23, %24, %25, %26, %27, %28, %29, %30, %31, %32, %33, %34, %35, %36, %37, %38, %39, %40, %41, %42, %43, %44, %45, %46, %47, %48, %49, %50, %51, %52, %53, %54, %55, %56, %57, %58, %59, %60, %61, %62, %63, %64, %65, %66, %67, %68, %69, %70, %71, %72, %73, %74, %75, %76, %77, %78, %79, %80, %81, %82, %83, %84, %85, %86, %87, %88, %89, %90, %91, %92, %93, %94, %95, %96, %97, %98, %99, %100, %101, %102, %103, %104, %105, %106, %107, %108, %109, %110, %111, %112, %113, %114, %115, %116, %117, %118, %119, %120, %121, %122, %123, %124, %125, %126, %127}, da, db, p, 1, 1, 0, 0;\n}\n"
    : "+f"(d[0]), "+f"(d[1]), "+f"(d[2]), "+f"(d[3]), "+f"(d[4]), "+f"(d[5]), "+f"(d[6]), "+f"(d[7]), "+f"(d[8]), "+f"(d[9]), "+f"(d[10]), "+f"(d[11]), "+f"(d[12]), "+f"(d[13]), "+f"(d[14]), "+f"(d[15]), "+f"(d[16]), "+f"(d[17]), "+f"(d[18]), "+f"(d[19]), "+f"(d[20]), "+f"(d[21]), "+f"(d[22]), "+f"(d[23]), "+f"(d[24]), "+f"(d[25]), "+f"(d[26]), "+f"(d[27]), "+f"(d[28]), "+f"(d[29]), "+f"(d[30]), "+f"(d[31]), "+f"(d[32]), "+f"(d[33]), "+f"(d[34]), "+f"(d[35]), "+f"(d[36]), "+f"(d[37]), "+f"(d[38]), "+f"(d[39]), "+f"(d[40]), "+f"(d[41]), "+f"(d[42]), "+f"(d[43]), "+f"(d[44]), "+f"(d[45]), "+f"(d[46]), "+f"(d[47]), "+f"(d[48]), "+f"(d[49]), "+f"(d[50]), "+f"(d[51]), "+f"(d[52]), "+f"(d[53]), "+f"(d[54]), "+f"(d[55]), "+f"(d[56]), "+f"(d[57]), "+f"(d[58]), "+f"(d[59]), "+f"(d[60]), "+f"(d[61]), "+f"(d[62]), "+f"(d[63]), "+f"(d[64]), "+f"(d[65]), "+f"(d[66]), "+f"(d[67]), "+f"(d[68]), "+f"(d[69]), "+f"(d[70]), "+f"(d[71]), "+f"(d[72]), "+f"(d[73]), "+f"(d[74]), "+f"(d[75]), "+f"(d[76]), "+f"(d[77]), "+f"(d[78]), "+f"(d[79]), "+f"(d[80]), "+f"(d[81]), "+f"(d[82]), "+f"(d[83]), "+f"(d[84]), "+f"(d[85]), "+f"(d[86]), "+f"(d[87]), "+f"(d[88]), "+f"(d[89]), "+f"(d[90]), "+f"(d[91]), "+f"(d[92]), "+f"(d[93]), "+f"(d[94]), "+f"(d[95]), "+f"(d[96]), "+f"(d[97]), "+f"(d[98]), "+f"(d[99]), "+f"(d[100]), "+f"(d[101]), "+f"(d[102]), "+f"(d[103]), "+f"(d[104]), "+f"(d[105]), "+f"(d[106]), "+f"(d[107]), "+f"(d[108]), "+f"(d[109]), "+f"(d[110]), "+f"(d[111]), "+f"(d[112]), "+f"(d[113]), "+f"(d[114]), "+f"(d[115]), "+f"(d[116]), "+f"(d[117]), "+f"(d[118]), "+f"(d[119]), "+f"(d[120]), "+f"(d[121]), "+f"(d[122]), "+f"(d[123]), "+f"(d[124]), "+f"(d[125]), "+f"(d[126]), "+f"(d[127])
    : "r"(da), "r"(db));
  }
}
template<bool INIT> __device__ __forceinline__ void wgmma_n128_nn(float* d, uint32_t da, uint32_t db) {
  if constexpr (INIT) {
  asm volatile("{\n.reg .pred p;\n.reg .b64 da, db;\nsetp.ne.b32 p, 0, 0;\nmov.b64 da, {%64, 8};\nmov.b64 db, {%65, 8};\nwgmma.mma_async.sync.aligned.m64n128k16.f32.bf16.bf16 {%0, %1, %2, %3, %4, %5, %6, %7, %8, %9, %10, %11, %12, %13, %14, %15, %16, %17, %18, %19, %20, %21, %22, %23, %24, %25, %26, %27, %28, %29, %30, %31, %32, %33, %34, %35, %36, %37, %38, %39, %40, %41, %42, %43, %44, %45, %46, %47, %48, %49, %50, %51, %52, %53, %54, %55, %56, %57, %58, %59, %60, %61, %62, %63}, da, db, p, 1, 1, 0, 0;\n}\n"
    : "=f"(d[0]), "=f"(d[1]), "=f"(d[2]), "=f"(d[3]), "=f"(d[4]), "=f"(d[5]), "=f"(d[6]), "=f"(d[7]), "=f"(d[8]), "=f"(d[9]), "=f"(d[10]), "=f"(d[11]), "=f"(d[12]), "=f"(d[13]), "=f"(d[14]), "=f"(d[15]), "=f"(d[16]), "=f"(d[17]), "=f"(d[18]), "=f"(d[19]), "=f"(d[20]), "=f"(d[21]), "=f"(d[22]), "=f"(d[23]), "=f"(d[24]), "=f"(d[25]), "=f"(d[26]), "=f"(d[27]), "=f"(d[28]), "=f"(d[29]), "=f"(d[30]), "=f"(d[31]), "=f"(d[32]), "=f"(d[33]), "=f"(d[34]), "=f"(d[35]), "=f"(d[36]), "=f"(d[37]), "=f"(d[38]), "=f"(d[39]), "=f"(d[40]), "=f"(d[41]), "=f"(d[42]), "=f"(d[43]), "=f"(d[44]), "=f"(d[45]), "=f"(d[46]), "=f"(d[47]), "=f"(d[48]), "=f"(d[49]), "=f"(d[50]), "=f"(d[51]), "=f"(d[52]), "=f"(d[53]), "=f"(d[54]), "=f"(d[55]), "=f"(d[56]), "=f"(d[57]), "=f"(d[58]), "=f"(d[59]), "=f"(d[60]), "=f"(d[61]), "=f"(d[62]), "=f"(d[63])
    : "r"(da), "r"(db));
  } else {
  asm volatile("{\n.reg .pred p;\n.reg .b64 da, db;\nsetp.ne.b32 p, 1, 0;\nmov.b64 da, {%64, 8};\nmov.b64 db, {%65, 8};\nwgmma.mma_async.sync.aligned.m64n128k16.f32.bf16.bf16 {%0, %1, %2, %3, %4, %5, %6, %7, %8, %9, %10, %11, %12, %13, %14, %15, %16, %17, %18, %19, %20, %21, %22, %23, %24, %25, %26, %27, %28, %29, %30, %31, %32, %33, %34, %35, %36, %37, %38, %39, %40, %41, %42, %43, %44, %45, %46, %47, %48, %49, %50, %51, %52, %53, %54, %55, %56, %57, %58, %59, %60, %61, %62, %63}, da, db, p, 1, 1, 0, 0;\n}\n"
    : "+f"(d[0]), "+f"(d[1]), "+f"(d[2]), "+f"(d[3]), "+f"(d[4]), "+f"(d[5]), "+f"(d[6]), "+f"(d[7]), "+f"(d[8]), "+f"(d[9]), "+f"(d[10]), "+f"(d[11]), "+f"(d[12]), "+f"(d[13]), "+f"(d[14]), "+f"(d[15]), "+f"(d[16]), "+f"(d[17]), "+f"(d[18]), "+f"(d[19]), "+f"(d[20]), "+f"(d[21]), "+f"(d[22]), "+f"(d[23]), "+f"(d[24]), "+f"(d[25]), "+f"(d[26]), "+f"(d[27]), "+f"(d[28]), "+f"(d[29]), "+f"(d[30]), "+f"(d[31]), "+f"(d[32]), "+f"(d[33]), "+f"(d[34]), "+f"(d[35]), "+f"(d[36]), "+f"(d[37]), "+f"(d[38]), "+f"(d[39]), "+f"(d[40]), "+f"(d[41]), "+f"(d[42]), "+f"(d[43]), "+f"(d[44]), "+f"(d[45]), "+f"(d[46]), "+f"(d[47]), "+f"(d[48]), "+f"(d[49]), "+f"(d[50]), "+f"(d[51]), "+f"(d[52]), "+f"(d[53]), "+f"(d[54]), "+f"(d[55]), "+f"(d[56]), "+f"(d[57]), "+f"(d[58]), "+f"(d[59]), "+f"(d[60]), "+f"(d[61]), "+f"(d[62]), "+f"(d[63])
    : "r"(da), "r"(db));
  }
}
template<bool INIT> __device__ __forceinline__ void wgmma_n64_tt(float* d, uint32_t da, uint32_t db) {
  if constexpr (INIT) {
  asm volatile("{\n.reg .pred p;\n.reg .b64 da, db;\nsetp.ne.b32 p, 0, 0;\nmov.b64 da, {%32, 0x40000040};\nmov.b64 db, {%33, 0x40000040};\nwgmma.mma_async.sync.aligned.m64n64k16.f32.bf16.bf16 {%0, %1, %2, %3, %4, %5, %6, %7, %8, %9, %10, %11, %12, %13, %14, %15, %16, %17, %18, %19, %20, %21, %22, %23, %24, %25, %26, %27, %28, %29, %30, %31}, da, db, p, 1, 1, 1, 1;\n}\n"
    : "=f"(d[0]), "=f"(d[1]), "=f"(d[2]), "=f"(d[3]), "=f"(d[4]), "=f"(d[5]), "=f"(d[6]), "=f"(d[7]), "=f"(d[8]), "=f"(d[9]), "=f"(d[10]), "=f"(d[11]), "=f"(d[12]), "=f"(d[13]), "=f"(d[14]), "=f"(d[15]), "=f"(d[16]), "=f"(d[17]), "=f"(d[18]), "=f"(d[19]), "=f"(d[20]), "=f"(d[21]), "=f"(d[22]), "=f"(d[23]), "=f"(d[24]), "=f"(d[25]), "=f"(d[26]), "=f"(d[27]), "=f"(d[28]), "=f"(d[29]), "=f"(d[30]), "=f"(d[31])
    : "r"(da), "r"(db));
  } else {
  asm volatile("{\n.reg .pred p;\n.reg .b64 da, db;\nsetp.ne.b32 p, 1, 0;\nmov.b64 da, {%32, 0x40000040};\nmov.b64 db, {%33, 0x40000040};\nwgmma.mma_async.sync.aligned.m64n64k16.f32.bf16.bf16 {%0, %1, %2, %3, %4, %5, %6, %7, %8, %9, %10, %11, %12, %13, %14, %15, %16, %17, %18, %19, %20, %21, %22, %23, %24, %25, %26, %27, %28, %29, %30, %31}, da, db, p, 1, 1, 1, 1;\n}\n"
    : "+f"(d[0]), "+f"(d[1]), "+f"(d[2]), "+f"(d[3]), "+f"(d[4]), "+f"(d[5]), "+f"(d[6]), "+f"(d[7]), "+f"(d[8]), "+f"(d[9]), "+f"(d[10]), "+f"(d[11]), "+f"(d[12]), "+f"(d[13]), "+f"(d[14]), "+f"(d[15]), "+f"(d[16]), "+f"(d[17]), "+f"(d[18]), "+f"(d[19]), "+f"(d[20]), "+f"(d[21]), "+f"(d[22]), "+f"(d[23]), "+f"(d[24]), "+f"(d[25]), "+f"(d[26]), "+f"(d[27]), "+f"(d[28]), "+f"(d[29]), "+f"(d[30]), "+f"(d[31])
    : "r"(da), "r"(db));
  }
}
template<bool INIT> __device__ __forceinline__ void wgmma_n8_tn(float* d, uint32_t da, uint32_t db) {
  if constexpr (INIT) {
  asm volatile("{\n.reg .pred p;\n.reg .b64 da, db;\nsetp.ne.b32 p, 0, 0;\nmov.b64 da, {%4, 0x40000040};\nmov.b64 db, {%5, 8};\nwgmma.mma_async.sync.aligned.m64n8k16.f32.bf16.bf16 {%0, %1, %2, %3}, da, db, p, 1, 1, 1, 0;\n}\n"
    : "=f"(d[0]), "=f"(d[1]), "=f"(d[2]), "=f"(d[3])
    : "r"(da), "r"(db));
  } else {
  asm volatile("{\n.reg .pred p;\n.reg .b64 da, db;\nsetp.ne.b32 p, 1, 0;\nmov.b64 da, {%4, 0x40000040};\nmov.b64 db, {%5, 8};\nwgmma.mma_async.sync.aligned.m64n8k16.f32.bf16.bf16 {%0, %1, %2, %3}, da, db, p, 1, 1, 1, 0;\n}\n"
    : "+f"(d[0]), "+f"(d[1]), "+f"(d[2]), "+f"(d[3])
    : "r"(da), "r"(db));
  }
}
template<bool INIT> __device__ __forceinline__ void wgmma_n40_tf32(float* d, const uint32_t* a, uint32_t db) {
  if constexpr (INIT) {
  asm volatile("{\n.reg .pred p;\n.reg .b64 db;\nsetp.ne.b32 p, 0, 0;\nmov.b64 db, {%24, 0x40000040};\nwgmma.mma_async.sync.aligned.m64n40k8.f32.tf32.tf32 {%0, %1, %2, %3, %4, %5, %6, %7, %8, %9, %10, %11, %12, %13, %14, %15, %16, %17, %18, %19}, {%20, %21, %22, %23}, db, p, 1, 1;\n}\n"
    : "=f"(d[0]), "=f"(d[1]), "=f"(d[2]), "=f"(d[3]), "=f"(d[4]), "=f"(d[5]), "=f"(d[6]), "=f"(d[7]), "=f"(d[8]), "=f"(d[9]), "=f"(d[10]), "=f"(d[11]), "=f"(d[12]), "=f"(d[13]), "=f"(d[14]), "=f"(d[15]), "=f"(d[16]), "=f"(d[17]), "=f"(d[18]), "=f"(d[19])
    : "r"(a[0]), "r"(a[1]), "r"(a[2]), "r"(a[3]), "r"(db));
  } else {
  asm volatile("{\n.reg .pred p;\n.reg .b64 db;\nsetp.ne.b32 p, 1, 0;\nmov.b64 db, {%24, 0x40000040};\nwgmma.mma_async.sync.aligned.m64n40k8.f32.tf32.tf32 {%0, %1, %2, %3, %4, %5, %6, %7, %8, %9, %10, %11, %12, %13, %14, %15, %16, %17, %18, %19}, {%20, %21, %22, %23}, db, p, 1, 1;\n}\n"
    : "+f"(d[0]), "+f"(d[1]), "+f"(d[2]), "+f"(d[3]), "+f"(d[4]), "+f"(d[5]), "+f"(d[6]), "+f"(d[7]), "+f"(d[8]), "+f"(d[9]), "+f"(d[10]), "+f"(d[11]), "+f"(d[12]), "+f"(d[13]), "+f"(d[14]), "+f"(d[15]), "+f"(d[16]), "+f"(d[17]), "+f"(d[18]), "+f"(d[19])
    : "r"(a[0]), "r"(a[1]), "r"(a[2]), "r"(a[3]), "r"(db));
  }
}

__device__ __forceinline__ void quad_transpose(uint32_t& r0, uint32_t& r1, uint32_t& r2, uint32_t& r3, int c) {
  bool o1 = c & 1, o2 = c & 2;
  uint32_t t0 = o1 ? r0 : r1, t1 = o1 ? r2 : r3;
  t0 = __shfl_xor_sync(~0u, t0, 1); t1 = __shfl_xor_sync(~0u, t1, 1);
  if (o1) { r0 = t0; r2 = t1; } else { r1 = t0; r3 = t1; }
  t0 = o2 ? r0 : r2; t1 = o2 ? r1 : r3;
  t0 = __shfl_xor_sync(~0u, t0, 2); t1 = __shfl_xor_sync(~0u, t1, 2);
  if (o2) { r0 = t0; r1 = t1; } else { r2 = t0; r3 = t1; }
}

__device__ __forceinline__ bool own_tile(int T) { return (0x0D0Cu >> T) & 1; }
__device__ __forceinline__ bool wide_tile(int T) { return (0x3939u >> T) & 1; }

template<int V> struct IntC { static constexpr int value = V; };

__device__ __forceinline__ const CUtensorMap* tile_info(const Params& prm, int T, int j, int rank, int& col) {
  const int tile = T & 7;
  col = 128 * j + 64 * rank;
  if (tile == 0) col = 1024 + 1024 * rank + 128 * j;
  if (tile < 2) return T < 8 ? &prm.wqkv_n : &prm.wqkv_p;
  if (tile == 2) return &prm.wo_p;
  if (tile == 7) return &prm.wd_p;
  col = 448 * j + 128 * (tile - 3);
  return rank ? &prm.wu_p : &prm.wg_p;
}

__device__ __forceinline__ void split3(float x, uint32_t& a, uint32_t& b, uint32_t& c) {
  a = pack_bf16(0.f, x); x -= __uint_as_float(a);
  b = pack_bf16(0.f, x); x -= __uint_as_float(b);
  c = pack_bf16(0.f, x);
}
__device__ __forceinline__ void tile_stats(const uint32_t* P, float2 (*st)[8], int row, int j, int c) {
  const float p0 = bf_lo(__shfl_sync(~0u, P[0], 0, 4)), p1 = bf_lo(__shfl_sync(~0u, P[4], 0, 4));
  float s0 = 0.f, s1 = 0.f, q0 = 0.f, q1 = 0.f;
#pragma unroll
  for (int b = 0; b < 16; b++) {
    const uint32_t u = P[(b >> 2) * 8 + (b & 3)], v = P[(b >> 2) * 8 + 4 + (b & 3)];
    float a0 = bf_lo(u) - p0, a1 = bf_hi(u) - p0, b0 = bf_lo(v) - p1, b1 = bf_hi(v) - p1;
    s0 += a0 + a1; s1 += b0 + b1;
    q0 = fmaf(a0, a0, fmaf(a1, a1, q0)); q1 = fmaf(b0, b0, fmaf(b1, b1, q1));
  }
  s0 += __shfl_xor_sync(~0u, s0, 1); s1 += __shfl_xor_sync(~0u, s1, 1);
  q0 += __shfl_xor_sync(~0u, q0, 1); q1 += __shfl_xor_sync(~0u, q1, 1);
  s0 += __shfl_xor_sync(~0u, s0, 2); s1 += __shfl_xor_sync(~0u, s1, 2);
  q0 += __shfl_xor_sync(~0u, q0, 2); q1 += __shfl_xor_sync(~0u, q1, 2);
  st_f2_if(&st[row][j], p0 + s0 * (1.f / 128.f), fmaxf(q0 - s0 * s0 * (1.f / 128.f), 0.f), c == 0);
  st_f2_if(&st[row + 8][j], p1 + s1 * (1.f / 128.f), fmaxf(q1 - s1 * s1 * (1.f / 128.f), 0.f), c == 0);
}

__device__ __forceinline__ void pack_half(const float* acc, uint32_t* PK) {
#pragma unroll
  for (int b = 0; b < 16; b++) {
    const int o = ((b >> 2) & 1) * 16 + (b >> 3) * 4 + (b & 3);
    PK[o] = pack_bf16(acc[4 * b], acc[4 * b + 1]);
    PK[o + 8] = pack_bf16(acc[4 * b + 2], acc[4 * b + 3]);
  }
}
template<int N> __device__ __forceinline__ void move_down(uint32_t* PK) {
#pragma unroll
  for (int q = 0; q < N; q++) asm volatile("mov.b32 %0, %1;" : "=r"(PK[q]) : "r"(PK[q + N]));
}
__device__ __forceinline__ void next_unit(uint32_t* PK, int u) {
  if (!(u & 1)) move_down<8>(PK); else if (!(u & 2)) move_down<16>(PK); else move_down<32>(PK);
}
__device__ __forceinline__ void lds_v4(uint32_t* v, uint32_t addr) {
  asm volatile("ld.shared.v4.u32 {%0, %1, %2, %3}, [%4];" : "=r"(v[0]), "=r"(v[1]), "=r"(v[2]), "=r"(v[3]) : "r"(addr) : "memory");
}
__device__ __forceinline__ void lds_tile(uint32_t* P, uint32_t b0, uint32_t b1, uint32_t ioff) {
#pragma unroll
  for (int q = 0; q < 8; q++) lds_v4(P + 4 * q, ((q >> 2) ? b1 : b0) + (q & 1) * 1024 + (ioff ^ ((q & 2) * 32)));
}
__device__ __forceinline__ void transpose_all(uint32_t* P, int c) {
#pragma unroll
  for (int q = 0; q < 8; q++) quad_transpose(P[4 * q], P[4 * q + 1], P[4 * q + 2], P[4 * q + 3], c);
}
__device__ __forceinline__ void add_residual(uint32_t* P, const float* acc) {
#pragma unroll
  for (int b = 0; b < 16; b++) {
    uint32_t& r0 = P[(b >> 2) * 8 + (b & 3)]; uint32_t& r1 = P[(b >> 2) * 8 + 4 + (b & 3)];
    r0 = hadd2(r0, pack_bf16(acc[4 * b], acc[4 * b + 1]));
    r1 = hadd2(r1, pack_bf16(acc[4 * b + 2], acc[4 * b + 3]));
  }
}
__device__ __forceinline__ float phi_s(float raw, float rstd, float rl2) { return fmaxf(fmaf(raw, rstd, 1.000001f), __saturatef(ex2f(raw * rl2) + 1e-6f)); }

template<bool HELPER>
__device__ __forceinline__ void colsum_warp(const Params& prm, uint32_t sb, uint32_t cbar, int id, int m, int j, int lane, uint32_t epoch) {
  const bool lead = elect_one();
  const int nbox = HELPER ? (id < 16 ? 48 : 40) : 2;
  float acc[8] = {};
  auto unit = [&](int b, int& col, int& kb, int& mat) {
    const int un = (b >> 3) * 48 + id, ch = un >> 1;
    kb = (un & 1) * 8 + (b & 7);
    if (ch < 16) col = ch * 64;
    else { const int q = ch - 16; mat = 1 + (q & 1); col = q < 96 ? 448 * ((q >> 2) & 7) + 128 * (q >> 5) + 32 * (q & 2) : 448 * ((q - 96) >> 1) + 384; }
  };
#pragma unroll 1
  for (int it = 0; it < 2 * nbox + 1; it++) {
    const int bx = it >> 1, k = it == 0 ? 0 : 1 - (it & 1);
    const int b = it == 0 ? 0 : k ? bx - 1 : bx + 1;
    if (b >= nbox) continue;
    int col, kb = m, mat = 0;
    if (HELPER) {
      unit(b, col, kb, mat);
    } else {
      col = 1024 + id * 1024 + 128 * j + b * 64;
    }
    const uint32_t sl = b & 1;
    if (k == 0) {
      if (lead) {
        mbar_expect_tx(cbar + 8 * sl, 8192);
        tma_5d(sb + sl * 8192, mat == 0 ? &prm.wqkv_n : mat == 1 ? &prm.wg_p : &prm.wu_p, cbar + 8 * sl, col, kb * 2);
      }
    } else {
      mbar_wait(cbar + 8 * sl, (b >> 1) & 1);
      const uint32_t ad = sb + sl * 8192 + (lane >> 3) * 128;
#pragma unroll 2
      for (int q = 0; q < 8; q++) {
        uint4 v, w;
        asm volatile("ld.shared.v4.u32 {%0, %1, %2, %3}, [%4];" : "=r"(v.x), "=r"(v.y), "=r"(v.z), "=r"(v.w) : "r"(ad + q * 1024 + (((lane & 7) ^ (lane >> 3)) << 4)) : "memory");
        asm volatile("ld.shared.v4.u32 {%0, %1, %2, %3}, [%4];" : "=r"(w.x), "=r"(w.y), "=r"(w.z), "=r"(w.w) : "r"(ad + q * 1024 + 512 + (((lane & 7) ^ (lane >> 3) ^ 4) << 4)) : "memory");
        acc[0] += bf_lo(v.x) + bf_lo(w.x); acc[1] += bf_hi(v.x) + bf_hi(w.x); acc[2] += bf_lo(v.y) + bf_lo(w.y); acc[3] += bf_hi(v.y) + bf_hi(w.y);
        acc[4] += bf_lo(v.z) + bf_lo(w.z); acc[5] += bf_hi(v.z) + bf_hi(w.z); acc[6] += bf_lo(v.w) + bf_lo(w.w); acc[7] += bf_hi(v.w) + bf_hi(w.w);
      }
      __syncwarp();
      if (!HELPER || (b & 7) == 7) {
#pragma unroll
        for (int q = 0; q < 8; q++) { acc[q] += __shfl_xor_sync(~0u, acc[q], 8); acc[q] += __shfl_xor_sync(~0u, acc[q], 16); }
        float* dst = &prm.sc->cs[epoch & 1][(mat == 0 ? 0 : mat == 1 ? 3072 : 3072 + F_) + col + 8 * (lane & 7)];
        if (lane < 8) { red_add_v4(dst, acc[0], acc[1], acc[2], acc[3]); red_add_v4(dst + 4, acc[4], acc[5], acc[6], acc[7]); }
#pragma unroll
        for (int q = 0; q < 8; q++) acc[q] = 0.f;
        if (b == nbox - 1 || (HELPER && (b < 16 || b == 31))) {
          __syncwarp();
          if (lead) { fence_gpu(); red_add_u32(&prm.sc->cscnt[HELPER ? (b > 31 ? 11 : 8 + ((b + 1) >> 4)) : j][0], 1); }
        }
      }
    }
  }
}

#define TR(i)

__global__ void __launch_bounds__(384, 1) fused_kernel(const __grid_constant__ Params prm) {
  extern __shared__ __align__(1024) uint8_t smem_raw[];
#define SMEM_ADDRS \
const uint32_t sbase = __shfl_sync(~0u, smem_u32(smem_raw), 0); \
  const uint32_t full = sbase + OFF_BAR, empty = full + 64; \
  const uint32_t bar_kvdone = full + 128, bar_kvready = full + 136, bar_sig = full + 144; \
  const uint32_t bar_sig2 = full + 160, bar_cs = full + 176, bar_res = full + 216, bar_ln = full + 416;
  const int warp = __shfl_sync(~0u, threadIdx.x >> 5, 0);
  const bool helper = blockIdx.x < 4;
#define ROLE_IDS \
  int bid; asm volatile("mov.u32 %0, %%ctaid.x;" : "=r"(bid)); \
  const int rank = bid & 1, role = prm.role[bid >> 1], mp = role & 7, j = role >> 3; \
  const int m = mp * 2 + rank, cta = m * 8 + j;

  {
  SMEM_ADDRS
  ROLE_IDS
  if (elect_one()) {
    if (!helper) {
      const int q = m >> 2, kb = 2 * ((q >> 1) + ((q >> 1) >= j)) + (q & 1);
      if (warp == 1) asm volatile("cp.async.bulk.prefetch.tensor.2d.L2.global.tile [%0, {%1, %2}];" :: "l"((uint64_t)&prm.x), "r"(j * 64), "r"(m * 128) : "memory");
      if (warp == 0) tma_5d_prefetch(&prm.wqkv_n, 1024 + 1024 * rank + 128 * j + (m & 2) * 32, kb * 2);
    }
#pragma unroll 1
    for (int t = warp; t < 53; t += 12) mbar_init(full + 8 * t, t < 8 ? 1 : t < 16 ? 4 : t == 16 ? 8 : (t >= 18 && t < 22) ? 4 : 1);
    asm volatile("fence.mbarrier_init.release.cluster;" ::: "memory");
  }
  }
  __syncwarp();
  asm volatile("barrier.cluster.arrive.relaxed.aligned;" ::: "memory");

  if (helper) {
    SMEM_ADDRS
    cluster_wait();
    colsum_warp<true>(prm, sbase + warp * 16384, full + 224 + warp * 16, blockIdx.x * 12 + warp, 0, 0, lane_id(), load_epoch());
  } else if (warp >= 4) {
    asm volatile("setmaxnreg.inc.sync.aligned.u32 232;");
    SMEM_ADDRS
    ROLE_IDS
    const int lane = lane_id();
    const int cw = (warp >> 2) - 1, w4 = warp & 3, g = lane >> 2, c = lane & 3;
    uint32_t PK[64];
    const uint32_t xoff = ((m * 128 + cw * 64 + w4 * 16 + g) * D_ + 128 * j + 8 * c) * 2;
    if (w4 < 2) sts_u32(sbase + OFF_ONES + (w4 * 32 + lane) * 4, 0x3F803F80u);
    cluster_wait();

    const bool relt = w4 == 0 && lane < 2;
    const uint32_t dones = make_desc(sbase + OFF_ONES, 128);
    {
      const int rloc = cw * 64 + w4 * 16 + g;
      const int row = m * 128 + rloc;
      const uint32_t ioff = rloc * 128 + ((c ^ g) << 4);
      const uint32_t tile_off = (m * 16 + 2 * j) * SLOT;
      const uint32_t da0 = make_desc(sbase + cw * 8192, 16), db0 = make_desc(sbase + SLOT, 8192);
      const uint32_t stg = sbase + OFF_STG + cw * 16384;
      const uint32_t rempty = mapa(empty, lane & 1);
      uint32_t n = 0, pos = 0;
      bool ok = false;
      float rstd0, rstd1;
      TR(0);
#pragma unroll 1
      for (int T = 0; T < 16; T++) {
        const int layer = T >> 3, tile = T & 7;
        const bool wide = wide_tile(T), own = own_tile(T);
        const int nsteps = tile == 7 ? 56 : 16;
        const bool lnin = tile == 0 || tile == 3;
        float2 (*st)[8] = prm.sc->stats[layer * 2 + (tile != 0)];
        if (tile == 3) { pos += 2048; if (pos >= NSLOT * 1024) pos -= NSLOT * 1024; }
        auto run = [&](auto WIDE_) {
          constexpr bool WIDE = decltype(WIDE_)::value;
          float acc[WIDE ? 128 : 64];
          auto kstep = [&](auto FIRST_, auto&& hook) {
            constexpr bool FIRST = decltype(FIRST_)::value;
            if (!ok) mbar_wait(full + 8 * (n & 7), (n >> 3) & 1);
            const uint32_t da = da0 + pos, db = db0 + pos;
            n++;
            pos += WIDE ? 3072 : 2048; if (pos >= NSLOT * 1024) pos -= NSLOT * 1024;
            KFENCE;
#pragma unroll
            for (int kk = 0; kk < 4; kk++) {
              if (FIRST && kk == 0) { if constexpr (WIDE) wgmma_n256_ss<true>(acc, da, db); else wgmma_n128_ss<true>(acc, da, db); }
              else { if constexpr (WIDE) wgmma_n256_ss<false>(acc, da + kk * 2, db + kk * 128); else wgmma_n128_ss<false>(acc, da + kk * 2, db + kk * 128); }
              if (kk == 1) {
                if constexpr (!FIRST) {
                  wgmma_commit();
                  wgmma_wait<1>();
                  mbar_arrive_remote_if(rempty + 8 * ((n - 2) & 7), relt);
                }
                ok = mbar_test(full + 8 * (n & 7), (n >> 3) & 1);
              }
              if (kk == 3) wgmma_commit();
              hook(kk);
            }
          };
          auto nohook = [](int) {};
          if (own) {
            uint8_t* img = (WIDE ? (tile == 0 ? prm.sc->x2 : prm.sc->x1) : prm.sc->o) + tile_off;
#pragma unroll
            for (int q = 0; q < 8; q++)
              *(uint4*)(img + (q >> 2) * SLOT + (q & 1) * 1024 + (ioff ^ ((q & 2) * 32))) = make_uint4(PK[4 * q], PK[4 * q + 1], PK[4 * q + 2], PK[4 * q + 3]);
            __syncwarp();
            mbar_arrive_if(bar_sig + 8 * cw, lane == 0);
            mbar_wait(full + 8 * (n & 7), (n >> 3) & 1);
            mbar_wait(full + 8 * ((n + 1) & 7), ((n + 1) >> 3) & 1);
            ok = true;
            uint32_t p1 = pos + (WIDE ? 3072 : 2048); if (p1 >= NSLOT * 1024) p1 -= NSLOT * 1024;
#pragma unroll
            for (int q = 0; q < 8; q++)
              sts_v4(sbase + ((q >> 2) ? p1 : pos) * 16 + (q & 1) * 1024 + (ioff ^ ((q & 2) * 32)), make_uint4(PK[4 * q], PK[4 * q + 1], PK[4 * q + 2], PK[4 * q + 3]));
            fence_async_smem();
            wg_bar(1 + cw);
          }
          kstep(IntC<1>{}, nohook);
          int i = 1;
          {
            if (tile >= 4) {
              uint32_t* t = PK;
              const int nu = tile == 6 ? 4 : 8;
              uint8_t* hb = prm.sc->h + (m * 56 + (tile - 4) * 16 + (tile == 7 ? j : 2 * j)) * SLOT;
              const int hb2 = tile == 7 ? (j - 15) * (int)SLOT : SLOT;
#pragma unroll 1
              for (int u = 0; u < nu; u++) {
                const float rstd = (u & 1) ? rstd1 : rstd0;
                const float ke = rstd * -1.4426950408889634f, iv = rcpf(rstd * rstd);
                auto glu = [&](int q) {
                  float s0 = rcpf(fmaf(ex2f(bf_lo(t[q]) * ke), iv, iv)), s1 = rcpf(fmaf(ex2f(bf_hi(t[q]) * ke), iv, iv));
                  t[q] = hmul2(hmul2(t[q], t[4 + q]), pack_bf16(s0, s1));
                };
                if constexpr (WIDE) kstep(IntC<0>{}, glu);
                else {
                  kstep(IntC<0>{}, [&](int q) { if (q & 1) glu(q >> 1); });
                  kstep(IntC<0>{}, [&](int q) { if (q & 1) glu(2 + (q >> 1)); });
                  i++;
                }
                *(uint4*)(hb + (u >> 2) * hb2 + (u & 1) * 1024 + (ioff ^ ((u & 2) * 32))) = make_uint4(t[0], t[1], t[2], t[3]);
                next_unit(PK, u);
                i++;
              }
              __syncwarp();
              mbar_arrive_if(bar_sig + 8 * cw, lane == 0);
            }
          }
          int stop = tile == 7 ? 24 + RSK * cw : T ? 2 : 5;
#pragma unroll 1
          for (int seg = 0; seg < 3; seg++) {
#pragma unroll 1
            for (; i < stop; i++) kstep(IntC<0>{}, nohook);
            if (seg == 0) {
              if (!WIDE && (tile == 2 || tile == 7)) {
                mbar_wait(bar_res, tile & 1);
                lds_tile(PK, sbase + OFF_STG, sbase + OFF_STG + SLOT, ioff);
                if (T == 2) transpose_all(PK, c);
              }
              if (WIDE && lnin) {
                if (T == 0) { mbar_wait(full + 40, 0); lds_tile(PK, sbase, sbase + 3 * SLOT, ioff); }
                tile_stats(PK, st, row, j, c);
                __syncwarp();
                mbar_arrive_if(bar_sig2 + 8 * cw, lane == 0);
              }
              stop = nsteps - (WIDE ? SKW : SKN);
            } else {
              if (HS && seg == 1 && cw == 1) asm volatile("bar.sync 3, 256;" ::: "memory");
              stop = nsteps;
            }
          }
          if (WIDE || tile == 1 || tile == 6) {
            if (WIDE && lnin) mbar_wait(bar_ln, tile != 0);
            if (tile != 6) mbar_wait(bar_cs + 8 * (tile - (tile > 2)), layer);
            const uint32_t dc = make_desc(sbase + (tile == 0 ? OFF_CSKV : tile == 1 ? OFF_CSQ : OFF_CSGU + (tile - 3) * 4096), 0);
            wgmma_fence();
            if constexpr (WIDE) wgmma_n256_nn<false>(acc, make_desc(sbase + OFF_LN + cw * 1024, 0), dc); else wgmma_n128_nn<false>(acc, make_desc(sbase + OFF_LN + cw * 1024, 0), dc);
            wgmma_commit();
            if (WIDE && lnin) {
              const uint32_t r0 = lds_u32(sbase + OFF_LN + rloc * 16 + 12), r1 = lds_u32(sbase + OFF_LN + rloc * 16 + 140);
              rstd0 = bf_lo(r0) + bf_hi(r0); rstd1 = bf_lo(r1) + bf_hi(r1);
            }
          }
          if (HS && cw == 0) asm volatile("bar.arrive 3, 256;" ::: "memory");
        wgmma_wait<0>();
        mbar_arrive_remote_if(rempty + 8 * ((n - 1) & 7), relt);
        TR(1 + 2 * T);
        if (!WIDE && (tile == 2 || tile == 7)) add_residual(PK, acc);
        else if (WIDE && tile == 0) {
          const float l0 = rstd0 * 1.4426950408889634f, l1 = rstd1 * 1.4426950408889634f;
          const uint32_t sta = stg + (w4 * 16 + ((lane >> 3) & 1) * 8 + (lane & 7)) * 128, da = make_desc(stg, 8192);
          float kv[2][32], z[2][4];
          if (cw == 0) asm volatile("bar.arrive 4, 256;" ::: "memory");
#pragma unroll
          for (int r = 0; r < 2; r++) {
            uint32_t* t = PK + 32 * r;
#pragma unroll
            for (int b = 0; b < 16; b++) {
              const float* a = acc + (WIDE ? 64 * r : 0) + 4 * b;
              const float v0 = a[0], v1 = a[1], v2 = a[2], v3 = a[3];
              if (b < 8) { t[2 * b] = pack_bf16(phi_s(v0, rstd0, l0), phi_s(v1, rstd0, l0)); t[2 * b + 1] = pack_bf16(phi_s(v2, rstd1, l1), phi_s(v3, rstd1, l1)); }
              else { t[2 * b] = pack_bf16(v0 * rstd0, v1 * rstd0); t[2 * b + 1] = pack_bf16(v2 * rstd1, v3 * rstd1); }
            }
            if (r) { wgmma_wait<0>(); wg_bar(1 + cw); }
            else if (cw == 1) asm volatile("bar.sync 4, 256;" ::: "memory");
#pragma unroll
            for (int b = 0; b < 16; b += 2)
              stmatrix_x4(sta + (b >> 3) * 8192 + ((((b & 7) + (lane >> 4)) ^ (lane & 7)) << 4), t[2 * b], t[2 * b + 1], t[2 * b + 2], t[2 * b + 3]);
            fence_async_smem();
            wg_bar(1 + cw);
            wgmma_fence();
            wgmma_n64_tt<true>(kv[r], da + 512, da);
            wgmma_n8_tn<true>(z[r], da, dones);
#pragma unroll
            for (int kk = 1; kk < 4; kk++) {
              wgmma_n64_tt<false>(kv[r], da + 512 + kk * 128, da + kk * 128);
              wgmma_n8_tn<false>(z[r], da + kk * 128, dones);
            }
            wgmma_commit();
          }
          wgmma_wait<0>();
          wg_bar(1 + cw);
          const uint32_t kb = stg + (w4 * 16 + g) * 128 + c * 4;
          float* zd = &prm.sc->kv[lds_u32(full + 480) & 1][layer][j][4096 + (w4 >> 1) * 32 + (w4 & 1) * 16 + (g & 1) * 4 + (g >> 1)];
#pragma unroll
          for (int r = 0; r < 2; r++) {
#pragma unroll
            for (int q = 0; q < 16; q++)
              sts_u32(kb + r * 8192 + (q & 2) * 512 + ((((q >> 2) * 2 + (q & 1)) ^ g) << 4), __float_as_uint(w4 >= 2 ? kv[r][16 + q] : kv[r][q]));
            red_add_f32_if(zd + 64 * r, z[r][0], c == 0); red_add_f32_if(zd + 64 * r + 8, z[r][2], c == 0);
          }
          fence_async_smem();
          __syncwarp();
          mbar_arrive_if(bar_kvdone, lane == 0);
        } else if (WIDE || tile != 1) {
          pack_half(acc, PK);
          if constexpr (WIDE) pack_half(acc + 64, PK + 32);
        } else {
          const float l0 = rstd0 * 1.4426950408889634f, l1 = rstd1 * 1.4426950408889634f;
#pragma unroll
          for (int b = 0; b < 16; b++) {
            PK[4 * b] = __float_as_uint(phi_s(acc[4 * b], rstd0, l0));
            PK[4 * b + 1] = __float_as_uint(phi_s(acc[4 * b + 2], rstd1, l1));
            PK[4 * b + 2] = __float_as_uint(phi_s(acc[4 * b + 1], rstd0, l0));
            PK[4 * b + 3] = __float_as_uint(phi_s(acc[4 * b + 3], rstd1, l1));
          }
          mbar_wait(bar_kvready, layer);
          float num[4][20];
          wgmma_fence();
#pragma unroll
          for (int ks = 0; ks < 4; ks++) {
#pragma unroll
            for (int hh = 0; hh < 4; hh++) {
              const uint32_t db = make_desc(sbase + OFF_STG + hh * 5120, 16) + 2 * ks;
              if (ks == 0) wgmma_n40_tf32<true>(num[hh], PK + 16 * hh, db); else wgmma_n40_tf32<false>(num[hh], PK + 16 * hh + 4 * ks, db);
            }
          }
          wgmma_commit();
          wgmma_wait<0>();
#pragma unroll
          for (int hh = 0; hh < 4; hh++) {
            const float* nm = num[hh];
            const float r0 = rcpf(__shfl_sync(~0u, nm[16], 0, 4) + 1e-6f), r1 = rcpf(__shfl_sync(~0u, nm[18], 0, 4) + 1e-6f);
#pragma unroll
            for (int b = 0; b < 4; b++) {
              PK[8 * hh + b] = pack_bf16(nm[4 * b] * r0, nm[4 * b + 1] * r0);
              PK[8 * hh + 4 + b] = pack_bf16(nm[4 * b + 2] * r1, nm[4 * b + 3] * r1);
            }
          }
        }
        };
        if (wide) run(IntC<1>{}); else run(IntC<0>{});
        TR(2 + 2 * T);
      }
      asm volatile("barrier.cluster.arrive.relaxed.aligned;" ::: "memory");
      transpose_all(PK, c);
#pragma unroll
      for (int q = 0; q < 8; q++)
        *(uint4*)((uint8_t*)prm.out + xoff + (q >> 1) * 64 + (q & 1) * 16 * D_) = make_uint4(PK[4 * q], PK[4 * q + 1], PK[4 * q + 2], PK[4 * q + 3]);
      if (cta == 0 && threadIdx.x == 128) prm.sc->epoch = lds_u32(full + 480);
    }
  } else {
    asm volatile("setmaxnreg.dec.sync.aligned.u32 40;");
    SMEM_ADDRS
    const int lane = lane_id();
    if (__builtin_expect(warp < 2, 1)) {
      ROLE_IDS
      uint32_t epoch = 0;
      uint32_t ready = 0, n = 0, dst = sbase;
      const bool lead = elect_one();
#pragma unroll 1
      for (int T = 0; T < 16; T++) {
        const int layer = T >> 3, tile = T & 7;
        const bool own = own_tile(T), wide = wide_tile(T);
        const uint32_t adv = (wide ? 3 : 2) * SLOT, dfill = wide ? 0x34000000u : 0x56000000u;
        uint32_t dtab = tile == 0 ? 0x34343445u : tile == 3 ? 0x34343334u : wide ? 0x34343434u : (tile == 1 || tile == 6) ? 0x56554534u : 0x56565656u;
        if (tile == 3) { dst += 2 * SLOT; if (dst >= sbase + NSLOT * SLOT) dst -= NSLOT * SLOT; }
        int col;
        const CUtensorMap* map = tile_info(prm, T, j, rank, col);
        const int kind = tile < 2 ? 3 : tile == 2 ? 0 : tile < 7 ? 1 : 2;
        const uint8_t* img = kind == 2 ? prm.sc->h + m * 56 * SLOT : (kind == 3 ? prm.sc->x2 : kind == 0 ? prm.sc->o : prm.sc->x1) + m * 16 * SLOT;
        const uint32_t* fl = &prm.sc->flag[layer][kind][m][lane];
        if ((0x8Du >> tile) & 1) ready = 0;
#pragma unroll 1
        for (int p = 0; p < (tile == 7 ? 28 : 8); p++) {
          const bool dummy = own && p == 0;
          int ab = p, kb, dk = 1;
          uint32_t need;
          if (tile == 7) {
            kb = p < 24 ? 7 * (p & 7) + 2 * (p >> 3) : 14 * p - 330; dk = p < 24 ? 1 : 7;
            need = p < 16 ? 1u << p : p < 24 ? 0x101u << p : 3u << (2 * p - 24);
          } else {
            if (own || T == 0) { const int po = T ? 0 : 2, q = p - (p > po); ab = p == po ? j : q + (q >= j); }
            kb = 2 * ab;
            need = (dummy || T < 2) ? 0u : 1u << ab;
          }
          if (n == 4) epoch = load_epoch();
          if (warp && (ready & need) != need) {
            uint32_t tries = 0;
            do {
              ready = __ballot_sync(~0u, POLL(fl) == epoch);
              if (++tries > (1u << 20)) __trap();
            } while ((ready & need) != need);
            fence_async_global();
          }
          const uint8_t* src = img + ab * 2 * SLOT;
          const int X0 = n - (dtab & 15), X1 = n - ((dtab >> 4) & 15);
          dtab = (dtab >> 8) | dfill;
          const uint32_t fb = full + 8 * (n & 7);
          uint32_t dst1 = dst + adv; if (dst1 >= sbase + NSLOT * SLOT) dst1 -= NSLOT * SLOT;
          if (n == 0) cluster_wait();
          if (warp == 0) {
            const uint32_t bytes = dummy ? adv - SLOT : adv;
            if (n >= 4) mbar_wait(empty + 8 * (X0 & 7), (X0 >> 3) & 1);
            if (lead) {
              mbar_expect_tx(fb, bytes);
              tma_5d_mc(dst + SLOT + rank * 8192, map, fb, col, kb * 2);
              if (wide) tma_5d_mc(dst + 2 * SLOT + rank * 8192, map, fb, col + 64, kb * 2);
            }
            if (n >= 4) mbar_wait(empty + 8 * (X1 & 7), (X1 >> 3) & 1);
            if (lead) {
              mbar_expect_tx(fb + 8, bytes);
              tma_5d_mc(dst1 + SLOT + rank * 8192, map, fb + 8, col, (kb + dk) * 2);
              if (wide) tma_5d_mc(dst1 + 2 * SLOT + rank * 8192, map, fb + 8, col + 64, (kb + dk) * 2);
            }
          } else if (!dummy) {
            if (n >= 4) mbar_wait(empty + 8 * (X0 & 7), (X0 >> 3) & 1);
            if (lead) { if (T < 2) tma_2d(dst, &prm.x, fb, kb * 64, m * 128); else bulk_load(dst, src, SLOT, fb); }
            if (n >= 4) mbar_wait(empty + 8 * (X1 & 7), (X1 >> 3) & 1);
            if (lead) { if (T < 2) tma_2d(dst1, &prm.x, fb + 8, kb * 64 + 64, m * 128); else bulk_load(dst1, src + SLOT, SLOT, fb + 8); }
          }
          n += 2;
          dst = dst1 + adv; if (dst >= sbase + NSLOT * SLOT) dst -= NSLOT * SLOT;
        }
      }
    } else {
      const int w = warp - 2;
      ROLE_IDS
      cluster_wait();
      const uint32_t epoch = load_epoch();
      sts_u32(full + 480, epoch);
      mbar_wait(full, 0);
      colsum_warp<false>(prm, sbase + OFF_STG + w * 16384, full + 224 + warp * 16, w, m, j, lane, epoch);
      {
        float* z = &prm.sc->kv[(epoch & 1) ^ 1][0][0][0] + (size_t)cta * 528;
        for (int i = w * 32 + lane; i < 132; i += 64) *(float4*)(z + i * 4) = make_float4(0.f, 0.f, 0.f, 0.f);
        if (w && lane < 20) *(float4*)&prm.sc->cs[(epoch & 1) ^ 1][cta * 80 + lane * 4] = make_float4(0.f, 0.f, 0.f, 0.f);
      }
      if (w == 0) {
        int pf = 1;
        uint32_t sigph = 0;
#pragma unroll 1
        for (int ev = 1; ev < 18; ev++) {
          const int layer = ev >= 9, e = ev - 9 * layer;
          const bool se = e == 1 || e == 4;
          const uint32_t sb = se ? bar_sig2 : bar_sig, sp = se ? e >> 2 : sigph;
          const int kind = (0x222211033ull >> (4 * e)) & 3, sub = (0x321010010ull >> (4 * e)) & 3;
          uint32_t* f = &prm.sc->flag[layer][kind][m][sub * 8 + j];
          mbar_wait(sb, sp); mbar_wait(sb + 8, sp);
          if ((e == 2 || e == 8) && lane == 0) {
            mbar_expect_tx(bar_res, 2 * SLOT);
            if (ev == 2) { tma_2d(sbase + OFF_STG, &prm.x, bar_res, 128 * j, m * 128); tma_2d(sbase + OFF_STG + SLOT, &prm.x, bar_res, 128 * j + 64, m * 128); }
            else bulk_load(sbase + OFF_STG, (e == 2 ? prm.sc->x2 : prm.sc->x1) + (m * 16 + 2 * j) * SLOT, 2 * SLOT, bar_res);
          }
          if (lane == 0) { fence_gpu(); st_relaxed(f, epoch); fence_async_global(); }
          if (!se) sigph ^= 1;
          const int hi = min(16, layer * 8 + (int)((PFTAB >> (4 * e)) & 15));
#pragma unroll 1
          for (; pf < hi; pf++) {
            int col;
            const CUtensorMap* map = tile_info(prm, pf, j, rank, col);
#pragma unroll 1
            for (int kb = mp; kb < ((pf & 7) == 7 ? 56 : 16); kb += 8) {
              if (lane == 0) { tma_5d_prefetch(map, col, kb * 2); if (wide_tile(pf)) tma_5d_prefetch(map, col + 64, kb * 2); }
              __nanosleep(PFSLEEP);
            }
          }
          __syncwarp();
        }
      } else {
#pragma unroll 1
        for (int rr = 0; rr < 10; rr++) {
          const int layer = rr >= 5, r = rr - 5 * layer;
          const bool lnr = r == 0 || r == 2;
          if (lnr) { mbar_wait(bar_sig2, r >> 1); mbar_wait(bar_sig2 + 8, r >> 1); }
          if (r == 1) {
            float* kvp = prm.sc->kv[epoch & 1][layer][j];
            mbar_wait(bar_kvdone, layer);
            if (lane == 0) {
              bulk_reduce_f32(kvp, sbase + OFF_STG, 16384);
              bulk_reduce_f32(kvp, sbase + OFF_STG + 16384, 16384);
              asm volatile("cp.async.bulk.commit_group;\ncp.async.bulk.wait_group 0;" ::: "memory");
              fence_gpu();
              red_add_u32(&prm.sc->kvcnt[layer][j][0], 1);
              mbar_expect_tx(bar_kvready, 16896);
            }
            __syncwarp();
          }
          poll_eq(&prm.sc->cscnt[r ? 7 + r : j][0], epoch * (r ? 48 : 32));
          {
            const int q0 = r > 2 ? 4 * r - 8 : 0, nq = (0x64424 >> (4 * r)) & 15;
            const uint32_t cb = full + 224 + 56, tmp = sbase + OFF_STG + 24576;
            fence_async_global();
            if (lane == 0) mbar_expect_tx(cb, nq * 256);
            __syncwarp();
            if (lane < nq) bulk_load(tmp + lane * 256, &prm.sc->cs[epoch & 1][(r == 0 ? 1024 + 128 * j : r == 1 ? 128 * j : 3072 + 448 * j + 32 * q0)
                                                                            + (lane & 1) * (r == 0 ? 1024 : r == 1 ? 64 : F_) + (lane >> 1) * 64], 256, cb);
            mbar_wait(cb, 1 ^ (rr & 1));
            const uint32_t ad = sbase + (r == 0 ? OFF_CSKV : r == 1 ? OFF_CSQ : OFF_CSGU) + q0 * 1024;
#pragma unroll 2
            for (int q = lane; q < 64 * nq; q += 32) {
              uint32_t c1, c2, c3;
              split3(__uint_as_float(lds_u32(tmp + q * 4)), c1, c2, c3);
              sts_v4(ad + q * 16, make_uint4(c2 | (c1 >> 16), c3 | (c1 >> 16), c1 | (c2 >> 16), 0));
            }
          }
          fence_async_smem();
          __syncwarp();
          if (lane == 0) mbar_arrive(bar_cs + 8 * r);
          if (lnr) {
            poll_eq(&prm.sc->flag[layer][r ? 1 : 3][m][8 + (lane & 7)], epoch);
            __syncwarp();
            const uint32_t lb = full + 224 + 48;
            if (lane == 0) {
              fence_async_global();
              mbar_expect_tx(lb, 8192);
              bulk_load(sbase + OFF_STG + 16384, prm.sc->stats[layer * 2 + (r >> 1)][m * 128], 8192, lb);
            }
            mbar_wait(lb, 1 ^ (r >> 1));
#pragma unroll 1
            for (int q = 0; q < 4; q++) {
              float4 t0, t1, t2, t3;
              const uint32_t sp = sbase + OFF_STG + 16384 + (q * 32 + lane) * 64;
              lds_v4((uint32_t*)&t0, sp + ((lane << 3) & 48)); lds_v4((uint32_t*)&t1, sp + (((lane << 3) + 16) & 48));
              lds_v4((uint32_t*)&t2, sp + (((lane << 3) + 32) & 48)); lds_v4((uint32_t*)&t3, sp + (((lane << 3) + 48) & 48));
              const float mean = ((t0.x + t0.z) + (t1.x + t1.z) + (t2.x + t2.z) + (t3.x + t3.z)) * 0.125f;
              auto sq = [&](float v) { return (v - mean) * (v - mean); };
              const float m2 = (t0.y + t0.w) + (t1.y + t1.w) + (t2.y + t2.w) + (t3.y + t3.w)
                             + 128.f * (sq(t0.x) + sq(t0.z) + sq(t1.x) + sq(t1.z) + sq(t2.x) + sq(t2.z) + sq(t3.x) + sq(t3.z));
              uint32_t a1, a2, a3, r1, r2, r3;
              split3(-0.5f * mean, a1, a2, a3);
              split3(rsqrtf(m2 * (1.f / 1024.f) + 1e-5f), r1, r2, r3);
              sts_v4(sbase + OFF_LN + (q * 32 + lane) * 16, make_uint4(a1 | (a1 >> 16), a1 | (a2 >> 16), a3 | (a2 >> 16), r1 | (r2 >> 16)));
            }
            fence_async_smem();
            __syncwarp();
            if (lane == 0) mbar_arrive(bar_ln);
          }
          if (r == 1) {
            float* kvp = prm.sc->kv[epoch & 1][layer][j];
            poll_eq(&prm.sc->kvcnt[layer][j][0], epoch * 16);
            fence_async_global();
            if (lane < 8) bulk_load(sbase + OFF_STG + (lane & 3) * 5120 + (lane >> 2) * 4096, kvp + (lane < 4 ? lane * 1024 : 4096 + (lane & 3) * 32), lane < 4 ? 4096 : 128, bar_kvready);
            __syncwarp();
          }
        }
      }
    }
  }
  __syncwarp();
  if (helper || warp < 4) asm volatile("barrier.cluster.arrive.relaxed.aligned;" ::: "memory");
  cluster_wait();
}

typedef CUresult (*EncodeTiledFn)(CUtensorMap*, CUtensorMapDataType, cuuint32_t, void*, const cuuint64_t*, const cuuint64_t*, const cuuint32_t*, const cuuint32_t*,
                                  CUtensorMapInterleave, CUtensorMapSwizzle, CUtensorMapL2promotion, CUtensorMapFloatOOBfill);

void make_wmap(EncodeTiledFn enc, CUtensorMap* m, const void* ptr, uint64_t rows, uint64_t cols, bool perm) {
  uint64_t rs = cols * 2;
  cuuint64_t gd[5] = {cols, 2, 4, 4, rows / 32};
  cuuint64_t gs[4] = {rs, (perm ? 8 : 2) * rs, (perm ? 2 : 8) * rs, 32 * rs};
  cuuint32_t bd[5] = {64, 2, 4, 4, 2}, es[5] = {1, 1, 1, 1, 1};
  enc(m, CU_TENSOR_MAP_DATA_TYPE_BFLOAT16, 5, (void*)ptr, gd, gs, bd, es, CU_TENSOR_MAP_INTERLEAVE_NONE, CU_TENSOR_MAP_SWIZZLE_128B,
      CU_TENSOR_MAP_L2_PROMOTION_L2_256B, CU_TENSOR_MAP_FLOAT_OOB_FILL_NONE);
}

void make_2d(EncodeTiledFn enc, CUtensorMap* m, const void* ptr, uint64_t rows, uint64_t cols, uint32_t box_rows) {
  cuuint64_t gd[2] = {cols, rows}, gs[1] = {cols * 2}; cuuint32_t bd[2] = {64, box_rows}, es[2] = {1, 1};
  enc(m, CU_TENSOR_MAP_DATA_TYPE_BFLOAT16, 2, (void*)ptr, gd, gs, bd, es, CU_TENSOR_MAP_INTERLEAVE_NONE, CU_TENSOR_MAP_SWIZZLE_128B,
      CU_TENSOR_MAP_L2_PROMOTION_L2_256B, CU_TENSOR_MAP_FLOAT_OOB_FILL_NONE);
}

}

extern "C" void kernel_launch(void* const* d_in, const int* in_sizes, int n_in, void* d_out, int out_size) {
  const __nv_bfloat16* x = (const __nv_bfloat16*)d_in[0];
  const __nv_bfloat16* wqkv = (const __nv_bfloat16*)d_in[1];
  const __nv_bfloat16* wo = (const __nv_bfloat16*)d_in[2];
  const __nv_bfloat16* wg = (const __nv_bfloat16*)d_in[4];
  const __nv_bfloat16* wu = (const __nv_bfloat16*)d_in[5];
  const __nv_bfloat16* wd = (const __nv_bfloat16*)d_in[6];

  void* fn = nullptr; cudaDriverEntryPointQueryResult qr;
  cudaGetDriverEntryPoint("cuTensorMapEncodeTiled", &fn, cudaEnableDefault, &qr);
  EncodeTiledFn enc = (EncodeTiledFn)fn;
  Params prm;
  make_2d(enc, &prm.x, x, S_, D_, 128);
  make_wmap(enc, &prm.wqkv_n, wqkv, D_, 3 * D_, false);
  make_wmap(enc, &prm.wqkv_p, wqkv, D_, 3 * D_, true);
  make_wmap(enc, &prm.wo_p, wo, D_, D_, true);
  make_wmap(enc, &prm.wg_p, wg, D_, F_, true);
  make_wmap(enc, &prm.wu_p, wu, D_, F_, true);
  make_wmap(enc, &prm.wd_p, wd, F_, D_, true);
  prm.xin = x; prm.out = (__nv_bfloat16*)d_out;
  cudaGetSymbolAddress((void**)&prm.sc, g_scratch);
  for (int ci = 0; ci < 66; ci++) {
    const int tq = ci - 4;
    const int mp = (ci < 4 || ci >= 64) ? 0 : (tq < 32 ? tq & 7 : 1 + (tq - 32) % 7);
    const int j = ci < 4 ? 2 + ci : ci >= 64 ? ci - 58 : (tq < 32 ? tq >> 3 : 4 + (tq - 32) / 7);
    prm.role[ci] = mp | (j << 3);
  }

  cudaFuncSetAttribute(fused_kernel, cudaFuncAttributeMaxDynamicSharedMemorySize, SMEM_BYTES);
  cudaLaunchConfig_t cfg = {};
  cfg.gridDim = dim3(132); cfg.blockDim = dim3(384); cfg.dynamicSmemBytes = SMEM_BYTES; cfg.stream = cudaStreamPerThread;
  cudaLaunchAttribute at[1];
  at[0].id = cudaLaunchAttributeClusterDimension; at[0].val.clusterDim.x = 2; at[0].val.clusterDim.y = 1; at[0].val.clusterDim.z = 1;
  cfg.attrs = at; cfg.numAttrs = 1;
  cudaLaunchKernelEx(&cfg, fused_kernel, prm);
}
```

```cpp
#include <cuda_runtime.h>
#include <cuda_bf16.h>
#include <cuda.h>
#include <stdint.h>

namespace {

constexpr int S_ = 2048, D_ = 1024, F_ = 3584;
constexpr int NSLOT = 12;
constexpr uint32_t SLOT = 16384;
constexpr uint32_t OFF_STG = NSLOT * SLOT;
constexpr uint32_t OFF_LN = OFF_STG + 32768;
constexpr uint32_t OFF_ONES = OFF_LN + 2048;
constexpr uint32_t OFF_BAR = OFF_ONES + 256;
constexpr uint32_t SMEM_BYTES = OFF_BAR + 512;
constexpr uint32_t OFF_CSKV = OFF_STG + 28672, OFF_CSQ = OFF_STG + 20480, OFF_CSGU = OFF_STG;

struct RowBlock {
  uint8_t act[3][16 * SLOT];
  uint8_t h[56 * SLOT];
  float2 stats[4][128][8];
  uint32_t flag[2][4][32];
  uint8_t pad[(2u << 20) - 104 * SLOT - 32768 - 1024];
};
struct Scratch {
  RowBlock rb[16];
  float cs[2][3072 + 2 * F_];
  float kv[2][2][8][4224];
  uint32_t kvcnt[2][8][32];
  uint32_t cscnt[12][32];
  uint32_t epoch;
};
__device__ __align__(1024) uint8_t g_scratch[sizeof(Scratch) + (2u << 20)];

struct Params {
  CUtensorMap x, wqkv_n, wqkv_p, wo_p, wg_p, wu_p, wd_p;
  const __nv_bfloat16* xin;
  __nv_bfloat16* out;
  Scratch* sc;
  int role[66];
};

__device__ __forceinline__ uint32_t smem_u32(const void* p) { return (uint32_t)__cvta_generic_to_shared(p); }
__device__ __forceinline__ void mbar_init(uint32_t bar, uint32_t count) { asm volatile("mbarrier.init.shared::cta.b64 [%0], %1;" :: "r"(bar), "r"(count) : "memory"); }
__device__ __forceinline__ void mbar_expect_tx(uint32_t bar, uint32_t bytes) { asm volatile("mbarrier.arrive.expect_tx.shared::cta.b64 _, [%0], %1;" :: "r"(bar), "r"(bytes) : "memory"); }
__device__ __forceinline__ void mbar_arrive(uint32_t bar) { asm volatile("mbarrier.arrive.shared::cta.b64 _, [%0];" :: "r"(bar) : "memory"); }
__device__ __forceinline__ void mbar_arrive_cluster(uint32_t bar, uint32_t cta) {
  asm volatile("{\n.reg .b32 ra;\nmapa.shared::cluster.u32 ra, %0, %1;\nmbarrier.arrive.shared::cluster.b64 _, [ra];\n}\n" :: "r"(bar), "r"(cta) : "memory");
}
__device__ __forceinline__ void mbar_arrive_if(uint32_t bar, bool pred) {
  asm volatile("{\n.reg .pred p;\nsetp.ne.b32 p, %1, 0;\n@p mbarrier.arrive.shared::cta.b64 _, [%0];\n}\n" :: "r"(bar), "r"((uint32_t)pred) : "memory");
}
__device__ __forceinline__ void mbar_arrive_remote_if(uint32_t cluster_addr, bool pred) {
  asm volatile("{\n.reg .pred p;\nsetp.ne.b32 p, %1, 0;\n@p mbarrier.arrive.shared::cluster.b64 _, [%0];\n}\n" :: "r"(cluster_addr), "r"((uint32_t)pred) : "memory");
}
__device__ __forceinline__ uint32_t mapa(uint32_t addr, uint32_t cta) { uint32_t r; asm("mapa.shared::cluster.u32 %0, %1, %2;" : "=r"(r) : "r"(addr), "r"(cta)); return r; }
__device__ __forceinline__ void st_f2_if(float2* ptr, float a, float b, bool pred) {
  asm volatile("{\n.reg .pred p;\nsetp.ne.b32 p, %3, 0;\n@p st.global.v2.f32 [%0], {%1, %2};\n}\n" :: "l"(ptr), "f"(a), "f"(b), "r"((uint32_t)pred) : "memory");
}
__device__ __forceinline__ void stg_v4_if(void* ptr, const uint32_t* v, bool pred) {
  asm volatile("{\n.reg .pred p;\nsetp.ne.b32 p, %5, 0;\n@p st.global.v4.u32 [%0], {%1, %2, %3, %4};\n}\n" :: "l"(ptr), "r"(v[0]), "r"(v[1]), "r"(v[2]), "r"(v[3]), "r"((uint32_t)pred) : "memory");
}
__device__ __forceinline__ void red_add_f32_if(float* ptr, float v, bool pred) {
  asm volatile("{\n.reg .pred p;\nsetp.ne.b32 p, %2, 0;\n@p red.relaxed.gpu.global.add.f32 [%0], %1;\n}\n" :: "l"(ptr), "f"(v), "r"((uint32_t)pred) : "memory");
}
__device__ __forceinline__ void mbar_wait(uint32_t bar, uint32_t parity) {
  asm volatile("{\n.reg .pred p;\n.reg .b32 n;\nmov.b32 n, 0;\nWAIT_LOOP:\n"
               "mbarrier.try_wait.parity.shared::cta.b64 p, [%0], %1;\n@p bra WAIT_DONE;\n"
               "add.u32 n, n, 1;\nsetp.lt.u32 p, n, 1048576;\n@p bra WAIT_LOOP;\ntrap;\nWAIT_DONE:\n}\n" :: "r"(bar), "r"(parity) : "memory");
}
__device__ __forceinline__ uint32_t ld_acquire(const uint32_t* p) { uint32_t v; asm volatile("ld.acquire.gpu.global.u32 %0, [%1];" : "=r"(v) : "l"(p) : "memory"); return v; }
__device__ __forceinline__ uint32_t ld_relaxed(const uint32_t* p) { uint32_t v; asm volatile("ld.relaxed.gpu.global.u32 %0, [%1];" : "=r"(v) : "l"(p) : "memory"); return v; }
#define POLL ld_acquire
__device__ __forceinline__ void poll_eq(const uint32_t* p, uint32_t want) {
  uint32_t n = 0;
  while (ld_acquire(p) != want) { if (++n > (1u << 20)) __trap(); }
}
__device__ __forceinline__ void tma_2d(uint32_t dst, const CUtensorMap* m, uint32_t bar, int c0, int c1) {
  asm volatile("cp.async.bulk.tensor.2d.shared::cluster.global.mbarrier::complete_tx::bytes [%0], [%1, {%3, %4}], [%2];"
    :: "r"(dst), "l"((uint64_t)m), "r"(bar), "r"(c0), "r"(c1) : "memory");
}
__device__ __forceinline__ void tma_5d_mc(uint32_t dst, const CUtensorMap* m, uint32_t bar, int c0, int c4) {
  asm volatile("cp.async.bulk.tensor.5d.shared::cluster.global.mbarrier::complete_tx::bytes.multicast::cluster [%0], [%1, {%3, %5, %5, %5, %4}], [%2], %6;"
    :: "r"(dst), "l"((uint64_t)m), "r"(bar), "r"(c0), "r"(c4), "r"(0), "h"((uint16_t)3) : "memory");
}
__device__ __forceinline__ void tma_5d(uint32_t dst, const CUtensorMap* m, uint32_t bar, int c0, int c4) {
  asm volatile("cp.async.bulk.tensor.5d.shared::cluster.global.mbarrier::complete_tx::bytes [%0], [%1, {%3, %5, %5, %5, %4}], [%2];"
    :: "r"(dst), "l"((uint64_t)m), "r"(bar), "r"(c0), "r"(c4), "r"(0) : "memory");
}
__device__ __forceinline__ void tma_5d_prefetch(const CUtensorMap* m, int c0, int c4) {
  asm volatile("cp.async.bulk.prefetch.tensor.5d.L2.global.tile [%0, {%1, %3, %3, %3, %2}];" :: "l"((uint64_t)m), "r"(c0), "r"(c4), "r"(0) : "memory");
}
__device__ __forceinline__ void bulk_load(uint32_t dst, const void* src, uint32_t bytes, uint32_t bar) {
  asm volatile("cp.async.bulk.shared::cluster.global.mbarrier::complete_tx::bytes [%0], [%1], %2, [%3];"
    :: "r"(dst), "l"((uint64_t)src), "r"(bytes), "r"(bar) : "memory");
}
__device__ __forceinline__ void bulk_store(void* dst, uint32_t src, uint32_t bytes) {
  asm volatile("cp.async.bulk.global.shared::cta.bulk_group [%0], [%1], %2;" :: "l"((uint64_t)dst), "r"(src), "r"(bytes) : "memory");
}
#define SKW 1
#define SKN 1
#define KFENCE wgmma_fence()
#define HS 1
#define RSK 2
#define HLAST 1
#define SKR 4
#define PFSLEEP 500
#define PFTAB 0x9886544331ull
#define OWN_FENCE
__device__ __forceinline__ void bulk_reduce_f32(void* dst, uint32_t src, uint32_t bytes) {
  asm volatile("cp.reduce.async.bulk.global.shared::cta.bulk_group.add.f32 [%0], [%1], %2;" :: "l"((uint64_t)dst), "r"(src), "r"(bytes) : "memory");
}
__device__ __forceinline__ void wgmma_fence() { asm volatile("wgmma.fence.sync.aligned;" ::: "memory"); }
__device__ __forceinline__ void wgmma_commit() { asm volatile("wgmma.commit_group.sync.aligned;" ::: "memory"); }
template<int N> __device__ __forceinline__ void wgmma_wait() { asm volatile("wgmma.wait_group.sync.aligned %0;" :: "n"(N) : "memory"); }
__device__ __forceinline__ void cluster_sync() { asm volatile("barrier.cluster.arrive.release.aligned;\nbarrier.cluster.wait.acquire.aligned;" ::: "memory"); }
__device__ __forceinline__ void cluster_wait() { asm volatile("barrier.cluster.wait.acquire.aligned;" ::: "memory"); }
__device__ __forceinline__ void fence_async_smem() { asm volatile("fence.proxy.async.shared::cta;" ::: "memory"); }
__device__ __forceinline__ void fence_async_global() { asm volatile("fence.proxy.async.global;" ::: "memory"); }
__device__ __forceinline__ void fence_gpu() { asm volatile("fence.acq_rel.gpu;" ::: "memory"); }
__device__ __forceinline__ void wg_bar(int id) { asm volatile("bar.sync %0, 128;" :: "r"(id) : "memory"); }
__device__ __forceinline__ void st_relaxed(uint32_t* p, uint32_t v) { asm volatile("st.relaxed.gpu.global.u32 [%0], %1;" :: "l"(p), "r"(v) : "memory"); }
__device__ __forceinline__ void red_add_u32(uint32_t* p, uint32_t v) { asm volatile("red.relaxed.gpu.global.add.u32 [%0], %1;" :: "l"(p), "r"(v) : "memory"); }
__device__ __forceinline__ void red_add_f32(float* p, float v) { asm volatile("red.relaxed.gpu.global.add.f32 [%0], %1;" :: "l"(p), "f"(v) : "memory"); }
__device__ __forceinline__ void red_add_v4(float* p, float a, float b, float c, float d) {
  asm volatile("red.relaxed.gpu.global.add.v4.f32 [%0], {%1, %2, %3, %4};" :: "l"(p), "f"(a), "f"(b), "f"(c), "f"(d) : "memory");
}
__device__ __forceinline__ void stmatrix_x4(uint32_t addr, uint32_t r0, uint32_t r1, uint32_t r2, uint32_t r3) {
  asm volatile("stmatrix.sync.aligned.m8n8.x4.shared.b16 [%0], {%1, %2, %3, %4};" :: "r"(addr), "r"(r0), "r"(r1), "r"(r2), "r"(r3) : "memory");
}
__device__ __forceinline__ float2 lds_f2(uint32_t addr) { float2 v; asm volatile("ld.shared.v2.f32 {%0, %1}, [%2];" : "=f"(v.x), "=f"(v.y) : "r"(addr)); return v; }
__device__ __forceinline__ uint32_t lds_u32(uint32_t addr) { uint32_t v; asm volatile("ld.shared.u32 %0, [%1];" : "=r"(v) : "r"(addr) : "memory"); return v; }
__device__ __forceinline__ void sts_u32(uint32_t addr, uint32_t v) { asm volatile("st.shared.u32 [%0], %1;" :: "r"(addr), "r"(v) : "memory"); }
__device__ __forceinline__ void sts_v4(uint32_t addr, uint4 v) { asm volatile("st.shared.v4.u32 [%0], {%1, %2, %3, %4};" :: "r"(addr), "r"(v.x), "r"(v.y), "r"(v.z), "r"(v.w) : "memory"); }
__device__ __forceinline__ uint32_t pack_bf16(float lo, float hi) { uint32_t r; asm("cvt.rn.bf16x2.f32 %0, %1, %2;" : "=r"(r) : "f"(hi), "f"(lo)); return r; }
__device__ __forceinline__ float bf_lo(uint32_t v) { return __uint_as_float(v << 16); }
__device__ __forceinline__ float bf_hi(uint32_t v) { return __uint_as_float(v & 0xffff0000u); }
__device__ __forceinline__ float ex2f(float x) { float r; asm("ex2.approx.ftz.f32 %0, %1;" : "=f"(r) : "f"(x)); return r; }
__device__ __forceinline__ float rcpf(float x) { float r; asm("rcp.approx.ftz.f32 %0, %1;" : "=f"(r) : "f"(x)); return r; }
__device__ __forceinline__ float phif(float t) { return (t > 0.f ? t + 1.f : ex2f(t * 1.4426950408889634f)) + 1e-6f; }
__device__ __forceinline__ uint32_t make_desc(uint32_t addr, uint32_t lbo) { return ((addr & 0x3FFFF) >> 4) | ((lbo >> 4) << 16); }
__device__ __forceinline__ bool mbar_test(uint32_t bar, uint32_t parity) {
  uint32_t ok;
  asm volatile("{\n.reg .pred p;\nmbarrier.test_wait.parity.shared::cta.b64 p, [%1], %2;\nselp.u32 %0, 1, 0, p;\n}\n" : "=r"(ok) : "r"(bar), "r"(parity) : "memory");
  return ok;
}
__device__ __forceinline__ int lane_id() { int r; asm volatile("mov.u32 %0, %%laneid;" : "=r"(r)); return r; }
#define load_epoch() (__ldcg(&prm.sc->epoch) + 1)
__device__ __forceinline__ bool elect_one() {
  uint32_t r;
  asm volatile("{\n.reg .pred p;\nelect.sync _|p, 0xffffffff;\nselp.u32 %0, 1, 0, p;\n}\n" : "=r"(r));
  return r;
}
__device__ __forceinline__ uint32_t hadd2(uint32_t a, uint32_t b) { uint32_t r; asm("add.rn.bf16x2 %0, %1, %2;" : "=r"(r) : "r"(a), "r"(b)); return r; }
__device__ __forceinline__ uint32_t hmul2(uint32_t a, uint32_t b) { uint32_t r; asm("mul.rn.bf16x2 %0, %1, %2;" : "=r"(r) : "r"(a), "r"(b)); return r; }
__device__ __forceinline__ unsigned long long gtime() { unsigned long long t; asm volatile("mov.u64 %0, %%globaltimer;" : "=l"(t)); return t; }

template<bool INIT> __device__ __forceinline__ void wgmma_n256_ss(float* d, uint32_t da, uint32_t db) {
  if constexpr (INIT) {
  asm volatile("{\n.reg .pred p;\n.reg .b64 da, db;\nsetp.ne.b32 p, 0, 0;\nmov.b64 da, {%128, 0x40000040};\nmov.b64 db, {%129, 0x40000040};\nwgmma.mma_async.sync.aligned.m64n256k16.f32.bf16.bf16 {%0, %1, %2, %3, %4, %5, %6, %7, %8, %9, %10, %11, %12, %13, %14, %15, %16, %17, %18, %19, %20, %21, %22, %23, %24, %25, %26, %27, %28, %29, %30, %31, %32, %33, %34, %35, %36, %37, %38, %39, %40, %41, %42, %43, %44, %45, %46, %47, %48, %49, %50, %51, %52, %53, %54, %55, %56, %57, %58, %59, %60, %61, %62, %63, %64, %65, %66, %67, %68, %69, %70, %71, %72, %73, %74, %75, %76, %77, %78, %79, %80, %81, %82, %83, %84, %85, %86, %87, %88, %89, %90, %91, %92, %93, %94, %95, %96, %97, %98, %99, %100, %101, %102, %103, %104, %105, %106, %107, %108, %109, %110, %111, %112, %113, %114, %115, %116, %117, %118, %119, %120, %121, %122, %123, %124, %125, %126, %127}, da, db, p, 1, 1, 0, 1;\n}\n"
    : "=f"(d[0]), "=f"(d[1]), "=f"(d[2]), "=f"(d[3]), "=f"(d[4]), "=f"(d[5]), "=f"(d[6]), "=f"(d[7]), "=f"(d[8]), "=f"(d[9]), "=f"(d[10]), "=f"(d[11]), "=f"(d[12]), "=f"(d[13]), "=f"(d[14]), "=f"(d[15]), "=f"(d[16]), "=f"(d[17]), "=f"(d[18]), "=f"(d[19]), "=f"(d[20]), "=f"(d[21]), "=f"(d[22]), "=f"(d[23]), "=f"(d[24]), "=f"(d[25]), "=f"(d[26]), "=f"(d[27]), "=f"(d[28]), "=f"(d[29]), "=f"(d[30]), "=f"(d[31]), "=f"(d[32]), "=f"(d[33]), "=f"(d[34]), "=f"(d[35]), "=f"(d[36]), "=f"(d[37]), "=f"(d[38]), "=f"(d[39]), "=f"(d[40]), "=f"(d[41]), "=f"(d[42]), "=f"(d[43]), "=f"(d[44]), "=f"(d[45]), "=f"(d[46]), "=f"(d[47]), "=f"(d[48]), "=f"(d[49]), "=f"(d[50]), "=f"(d[51]), "=f"(d[52]), "=f"(d[53]), "=f"(d[54]), "=f"(d[55]), "=f"(d[56]), "=f"(d[57]), "=f"(d[58]), "=f"(d[59]), "=f"(d[60]), "=f"(d[61]), "=f"(d[62]), "=f"(d[63]), "=f"(d[64]), "=f"(d[65]), "=f"(d[66]), "=f"(d[67]), "=f"(d[68]), "=f"(d[69]), "=f"(d[70]), "=f"(d[71]), "=f"(d[72]), "=f"(d[73]), "=f"(d[74]), "=f"(d[75]), "=f"(d[76]), "=f"(d[77]), "=f"(d[78]), "=f"(d[79]), "=f"(d[80]), "=f"(d[81]), "=f"(d[82]), "=f"(d[83]), "=f"(d[84]), "=f"(d[85]), "=f"(d[86]), "=f"(d[87]), "=f"(d[88]), "=f"(d[89]), "=f"(d[90]), "=f"(d[91]), "=f"(d[92]), "=f"(d[93]), "=f"(d[94]), "=f"(d[95]), "=f"(d[96]), "=f"(d[97]), "=f"(d[98]), "=f"(d[99]), "=f"(d[100]), "=f"(d[101]), "=f"(d[102]), "=f"(d[103]), "=f"(d[104]), "=f"(d[105]), "=f"(d[106]), "=f"(d[107]), "=f"(d[108]), "=f"(d[109]), "=f"(d[110]), "=f"(d[111]), "=f"(d[112]), "=f"(d[113]), "=f"(d[114]), "=f"(d[115]), "=f"(d[116]), "=f"(d[117]), "=f"(d[118]), "=f"(d[119]), "=f"(d[120]), "=f"(d[121]), "=f"(d[122]), "=f"(d[123]), "=f"(d[124]), "=f"(d[125]), "=f"(d[126]), "=f"(d[127])
    : "r"(da), "r"(db));
  } else {
  asm volatile("{\n.reg .pred p;\n.reg .b64 da, db;\nsetp.ne.b32 p, 1, 0;\nmov.b64 da, {%128, 0x40000040};\nmov.b64 db, {%129, 0x40000040};\nwgmma.mma_async.sync.aligned.m64n256k16.f32.bf16.bf16 {%0, %1, %2, %3, %4, %5, %6, %7, %8, %9, %10, %11, %12, %13, %14, %15, %16, %17, %18, %19, %20, %21, %22, %23, %24, %25, %26, %27, %28, %29, %30, %31, %32, %33, %34, %35, %36, %37, %38, %39, %40, %41, %42, %43, %44, %45, %46, %47, %48, %49, %50, %51, %52, %53, %54, %55, %56, %57, %58, %59, %60, %61, %62, %63, %64, %65, %66, %67, %68, %69, %70, %71, %72, %73, %74, %75, %76, %77, %78, %79, %80, %81, %82, %83, %84, %85, %86, %87, %88, %89, %90, %91, %92, %93, %94, %95, %96, %97, %98, %99, %100, %101, %102, %103, %104, %105, %106, %107, %108, %109, %110, %111, %112, %113, %114, %115, %116, %117, %118, %119, %120, %121, %122, %123, %124, %125, %126, %127}, da, db, p, 1, 1, 0, 1;\n}\n"
    : "+f"(d[0]), "+f"(d[1]), "+f"(d[2]), "+f"(d[3]), "+f"(d[4]), "+f"(d[5]), "+f"(d[6]), "+f"(d[7]), "+f"(d[8]), "+f"(d[9]), "+f"(d[10]), "+f"(d[11]), "+f"(d[12]), "+f"(d[13]), "+f"(d[14]), "+f"(d[15]), "+f"(d[16]), "+f"(d[17]), "+f"(d[18]), "+f"(d[19]), "+f"(d[20]), "+f"(d[21]), "+f"(d[22]), "+f"(d[23]), "+f"(d[24]), "+f"(d[25]), "+f"(d[26]), "+f"(d[27]), "+f"(d[28]), "+f"(d[29]), "+f"(d[30]), "+f"(d[31]), "+f"(d[32]), "+f"(d[33]), "+f"(d[34]), "+f"(d[35]), "+f"(d[36]), "+f"(d[37]), "+f"(d[38]), "+f"(d[39]), "+f"(d[40]), "+f"(d[41]), "+f"(d[42]), "+f"(d[43]), "+f"(d[44]), "+f"(d[45]), "+f"(d[46]), "+f"(d[47]), "+f"(d[48]), "+f"(d[49]), "+f"(d[50]), "+f"(d[51]), "+f"(d[52]), "+f"(d[53]), "+f"(d[54]), "+f"(d[55]), "+f"(d[56]), "+f"(d[57]), "+f"(d[58]), "+f"(d[59]), "+f"(d[60]), "+f"(d[61]), "+f"(d[62]), "+f"(d[63]), "+f"(d[64]), "+f"(d[65]), "+f"(d[66]), "+f"(d[67]), "+f"(d[68]), "+f"(d[69]), "+f"(d[70]), "+f"(d[71]), "+f"(d[72]), "+f"(d[73]), "+f"(d[74]), "+f"(d[75]), "+f"(d[76]), "+f"(d[77]), "+f"(d[78]), "+f"(d[79]), "+f"(d[80]), "+f"(d[81]), "+f"(d[82]), "+f"(d[83]), "+f"(d[84]), "+f"(d[85]), "+f"(d[86]), "+f"(d[87]), "+f"(d[88]), "+f"(d[89]), "+f"(d[90]), "+f"(d[91]), "+f"(d[92]), "+f"(d[93]), "+f"(d[94]), "+f"(d[95]), "+f"(d[96]), "+f"(d[97]), "+f"(d[98]), "+f"(d[99]), "+f"(d[100]), "+f"(d[101]), "+f"(d[102]), "+f"(d[103]), "+f"(d[104]), "+f"(d[105]), "+f"(d[106]), "+f"(d[107]), "+f"(d[108]), "+f"(d[109]), "+f"(d[110]), "+f"(d[111]), "+f"(d[112]), "+f"(d[113]), "+f"(d[114]), "+f"(d[115]), "+f"(d[116]), "+f"(d[117]), "+f"(d[118]), "+f"(d[119]), "+f"(d[120]), "+f"(d[121]), "+f"(d[122]), "+f"(d[123]), "+f"(d[124]), "+f"(d[125]), "+f"(d[126]), "+f"(d[127])
    : "r"(da), "r"(db));
  }
}
template<bool INIT> __device__ __forceinline__ void wgmma_n128_ss(float* d, uint32_t da, uint32_t db) {
  if constexpr (INIT) {
  asm volatile("{\n.reg .pred p;\n.reg .b64 da, db;\nsetp.ne.b32 p, 0, 0;\nmov.b64 da, {%64, 0x40000040};\nmov.b64 db, {%65, 0x40000040};\nwgmma.mma_async.sync.aligned.m64n128k16.f32.bf16.bf16 {%0, %1, %2, %3, %4, %5, %6, %7, %8, %9, %10, %11, %12, %13, %14, %15, %16, %17, %18, %19, %20, %21, %22, %23, %24, %25, %26, %27, %28, %29, %30, %31, %32, %33, %34, %35, %36, %37, %38, %39, %40, %41, %42, %43, %44, %45, %46, %47, %48, %49, %50, %51, %52, %53, %54, %55, %56, %57, %58, %59, %60, %61, %62, %63}, da, db, p, 1, 1, 0, 1;\n}\n"
    : "=f"(d[0]), "=f"(d[1]), "=f"(d[2]), "=f"(d[3]), "=f"(d[4]), "=f"(d[5]), "=f"(d[6]), "=f"(d[7]), "=f"(d[8]), "=f"(d[9]), "=f"(d[10]), "=f"(d[11]), "=f"(d[12]), "=f"(d[13]), "=f"(d[14]), "=f"(d[15]), "=f"(d[16]), "=f"(d[17]), "=f"(d[18]), "=f"(d[19]), "=f"(d[20]), "=f"(d[21]), "=f"(d[22]), "=f"(d[23]), "=f"(d[24]), "=f"(d[25]), "=f"(d[26]), "=f"(d[27]), "=f"(d[28]), "=f"(d[29]), "=f"(d[30]), "=f"(d[31]), "=f"(d[32]), "=f"(d[33]), "=f"(d[34]), "=f"(d[35]), "=f"(d[36]), "=f"(d[37]), "=f"(d[38]), "=f"(d[39]), "=f"(d[40]), "=f"(d[41]), "=f"(d[42]), "=f"(d[43]), "=f"(d[44]), "=f"(d[45]), "=f"(d[46]), "=f"(d[47]), "=f"(d[48]), "=f"(d[49]), "=f"(d[50]), "=f"(d[51]), "=f"(d[52]), "=f"(d[53]), "=f"(d[54]), "=f"(d[55]), "=f"(d[56]), "=f"(d[57]), "=f"(d[58]), "=f"(d[59]), "=f"(d[60]), "=f"(d[61]), "=f"(d[62]), "=f"(d[63])
    : "r"(da), "r"(db));
  } else {
  asm volatile("{\n.reg .pred p;\n.reg .b64 da, db;\nsetp.ne.b32 p, 1, 0;\nmov.b64 da, {%64, 0x40000040};\nmov.b64 db, {%65, 0x40000040};\nwgmma.mma_async.sync.aligned.m64n128k16.f32.bf16.bf16 {%0, %1, %2, %3, %4, %5, %6, %7, %8, %9, %10, %11, %12, %13, %14, %15, %16, %17, %18, %19, %20, %21, %22, %23, %24, %25, %26, %27, %28, %29, %30, %31, %32, %33, %34, %35, %36, %37, %38, %39, %40, %41, %42, %43, %44, %45, %46, %47, %48, %49, %50, %51, %52, %53, %54, %55, %56, %57, %58, %59, %60, %61, %62, %63}, da, db, p, 1, 1, 0, 1;\n}\n"
    : "+f"(d[0]), "+f"(d[1]), "+f"(d[2]), "+f"(d[3]), "+f"(d[4]), "+f"(d[5]), "+f"(d[6]), "+f"(d[7]), "+f"(d[8]), "+f"(d[9]), "+f"(d[10]), "+f"(d[11]), "+f"(d[12]), "+f"(d[13]), "+f"(d[14]), "+f"(d[15]), "+f"(d[16]), "+f"(d[17]), "+f"(d[18]), "+f"(d[19]), "+f"(d[20]), "+f"(d[21]), "+f"(d[22]), "+f"(d[23]), "+f"(d[24]), "+f"(d[25]), "+f"(d[26]), "+f"(d[27]), "+f"(d[28]), "+f"(d[29]), "+f"(d[30]), "+f"(d[31]), "+f"(d[32]), "+f"(d[33]), "+f"(d[34]), "+f"(d[35]), "+f"(d[36]), "+f"(d[37]), "+f"(d[38]), "+f"(d[39]), "+f"(d[40]), "+f"(d[41]), "+f"(d[42]), "+f"(d[43]), "+f"(d[44]), "+f"(d[45]), "+f"(d[46]), "+f"(d[47]), "+f"(d[48]), "+f"(d[49]), "+f"(d[50]), "+f"(d[51]), "+f"(d[52]), "+f"(d[53]), "+f"(d[54]), "+f"(d[55]), "+f"(d[56]), "+f"(d[57]), "+f"(d[58]), "+f"(d[59]), "+f"(d[60]), "+f"(d[61]), "+f"(d[62]), "+f"(d[63])
    : "r"(da), "r"(db));
  }
}
template<bool INIT> __device__ __forceinline__ void wgmma_n256_nn(float* d, uint32_t da, uint32_t db) {
  if constexpr (INIT) {
  asm volatile("{\n.reg .pred p;\n.reg .b64 da, db;\nsetp.ne.b32 p, 0, 0;\nmov.b64 da, {%128, 8};\nmov.b64 db, {%129, 8};\nwgmma.mma_async.sync.aligned.m64n256k16.f32.bf16.bf16 {%0, %1, %2, %3, %4, %5, %6, %7, %8, %9, %10, %11, %12, %13, %14, %15, %16, %17, %18, %19, %20, %21, %22, %23, %24, %25, %26, %27, %28, %29, %30, %31, %32, %33, %34, %35, %36, %37, %38, %39, %40, %41, %42, %43, %44, %45, %46, %47, %48, %49, %50, %51, %52, %53, %54, %55, %56, %57, %58, %59, %60, %61, %62, %63, %64, %65, %66, %67, %68, %69, %70, %71, %72, %73, %74, %75, %76, %77, %78, %79, %80, %81, %82, %83, %84, %85, %86, %87, %88, %89, %90, %91, %92, %93, %94, %95, %96, %97, %98, %99, %100, %101, %102, %103, %104, %105, %106, %107, %108, %109, %110, %111, %112, %113, %114, %115, %116, %117, %118, %119, %120, %121, %122, %123, %124, %125, %126, %127}, da, db, p, 1, 1, 0, 0;\n}\n"
    : "=f"(d[0]), "=f"(d[1]), "=f"(d[2]), "=f"(d[3]), "=f"(d[4]), "=f"(d[5]), "=f"(d[6]), "=f"(d[7]), "=f"(d[8]), "=f"(d[9]), "=f"(d[10]), "=f"(d[11]), "=f"(d[12]), "=f"(d[13]), "=f"(d[14]), "=f"(d[15]), "=f"(d[16]), "=f"(d[17]), "=f"(d[18]), "=f"(d[19]), "=f"(d[20]), "=f"(d[21]), "=f"(d[22]), "=f"(d[23]), "=f"(d[24]), "=f"(d[25]), "=f"(d[26]), "=f"(d[27]), "=f"(d[28]), "=f"(d[29]), "=f"(d[30]), "=f"(d[31]), "=f"(d[32]), "=f"(d[33]), "=f"(d[34]), "=f"(d[35]), "=f"(d[36]), "=f"(d[37]), "=f"(d[38]), "=f"(d[39]), "=f"(d[40]), "=f"(d[41]), "=f"(d[42]), "=f"(d[43]), "=f"(d[44]), "=f"(d[45]), "=f"(d[46]), "=f"(d[47]), "=f"(d[48]), "=f"(d[49]), "=f"(d[50]), "=f"(d[51]), "=f"(d[52]), "=f"(d[53]), "=f"(d[54]), "=f"(d[55]), "=f"(d[56]), "=f"(d[57]), "=f"(d[58]), "=f"(d[59]), "=f"(d[60]), "=f"(d[61]), "=f"(d[62]), "=f"(d[63]), "=f"(d[64]), "=f"(d[65]), "=f"(d[66]), "=f"(d[67]), "=f"(d[68]), "=f"(d[69]), "=f"(d[70]), "=f"(d[71]), "=f"(d[72]), "=f"(d[73]), "=f"(d[74]), "=f"(d[75]), "=f"(d[76]), "=f"(d[77]), "=f"(d[78]), "=f"(d[79]), "=f"(d[80]), "=f"(d[81]), "=f"(d[82]), "=f"(d[83]), "=f"(d[84]), "=f"(d[85]), "=f"(d[86]), "=f"(d[87]), "=f"(d[88]), "=f"(d[89]), "=f"(d[90]), "=f"(d[91]), "=f"(d[92]), "=f"(d[93]), "=f"(d[94]), "=f"(d[95]), "=f"(d[96]), "=f"(d[97]), "=f"(d[98]), "=f"(d[99]), "=f"(d[100]), "=f"(d[101]), "=f"(d[102]), "=f"(d[103]), "=f"(d[104]), "=f"(d[105]), "=f"(d[106]), "=f"(d[107]), "=f"(d[108]), "=f"(d[109]), "=f"(d[110]), "=f"(d[111]), "=f"(d[112]), "=f"(d[113]), "=f"(d[114]), "=f"(d[115]), "=f"(d[116]), "=f"(d[117]), "=f"(d[118]), "=f"(d[119]), "=f"(d[120]), "=f"(d[121]), "=f"(d[122]), "=f"(d[123]), "=f"(d[124]), "=f"(d[125]), "=f"(d[126]), "=f"(d[127])
    : "r"(da), "r"(db));
  } else {
  asm volatile("{\n.reg .pred p;\n.reg .b64 da, db;\nsetp.ne.b32 p, 1, 0;\nmov.b64 da, {%128, 8};\nmov.b64 db, {%129, 8};\nwgmma.mma_async.sync.aligned.m64n256k16.f32.bf16.bf16 {%0, %1, %2, %3, %4, %5, %6, %7, %8, %9, %10, %11, %12, %13, %14, %15, %16, %17, %18, %19, %20, %21, %22, %23, %24, %25, %26, %27, %28, %29, %30, %31, %32, %33, %34, %35, %36, %37, %38, %39, %40, %41, %42, %43, %44, %45, %46, %47, %48, %49, %50, %51, %52, %53, %54, %55, %56, %57, %58, %59, %60, %61, %62, %63, %64, %65, %66, %67, %68, %69, %70, %71, %72, %73, %74, %75, %76, %77, %78, %79, %80, %81, %82, %83, %84, %85, %86, %87, %88, %89, %90, %91, %92, %93, %94, %95, %96, %97, %98, %99, %100, %101, %102, %103, %104, %105, %106, %107, %108, %109, %110, %111, %112, %113, %114, %115, %116, %117, %118, %119, %120, %121, %122, %123, %124, %125, %126, %127}, da, db, p, 1, 1, 0, 0;\n}\n"
    : "+f"(d[0]), "+f"(d[1]), "+f"(d[2]), "+f"(d[3]), "+f"(d[4]), "+f"(d[5]), "+f"(d[6]), "+f"(d[7]), "+f"(d[8]), "+f"(d[9]), "+f"(d[10]), "+f"(d[11]), "+f"(d[12]), "+f"(d[13]), "+f"(d[14]), "+f"(d[15]), "+f"(d[16]), "+f"(d[17]), "+f"(d[18]), "+f"(d[19]), "+f"(d[20]), "+f"(d[21]), "+f"(d[22]), "+f"(d[23]), "+f"(d[24]), "+f"(d[25]), "+f"(d[26]), "+f"(d[27]), "+f"(d[28]), "+f"(d[29]), "+f"(d[30]), "+f"(d[31]), "+f"(d[32]), "+f"(d[33]), "+f"(d[34]), "+f"(d[35]), "+f"(d[36]), "+f"(d[37]), "+f"(d[38]), "+f"(d[39]), "+f"(d[40]), "+f"(d[41]), "+f"(d[42]), "+f"(d[43]), "+f"(d[44]), "+f"(d[45]), "+f"(d[46]), "+f"(d[47]), "+f"(d[48]), "+f"(d[49]), "+f"(d[50]), "+f"(d[51]), "+f"(d[52]), "+f"(d[53]), "+f"(d[54]), "+f"(d[55]), "+f"(d[56]), "+f"(d[57]), "+f"(d[58]), "+f"(d[59]), "+f"(d[60]), "+f"(d[61]), "+f"(d[62]), "+f"(d[63]), "+f"(d[64]), "+f"(d[65]), "+f"(d[66]), "+f"(d[67]), "+f"(d[68]), "+f"(d[69]), "+f"(d[70]), "+f"(d[71]), "+f"(d[72]), "+f"(d[73]), "+f"(d[74]), "+f"(d[75]), "+f"(d[76]), "+f"(d[77]), "+f"(d[78]), "+f"(d[79]), "+f"(d[80]), "+f"(d[81]), "+f"(d[82]), "+f"(d[83]), "+f"(d[84]), "+f"(d[85]), "+f"(d[86]), "+f"(d[87]), "+f"(d[88]), "+f"(d[89]), "+f"(d[90]), "+f"(d[91]), "+f"(d[92]), "+f"(d[93]), "+f"(d[94]), "+f"(d[95]), "+f"(d[96]), "+f"(d[97]), "+f"(d[98]), "+f"(d[99]), "+f"(d[100]), "+f"(d[101]), "+f"(d[102]), "+f"(d[103]), "+f"(d[104]), "+f"(d[105]), "+f"(d[106]), "+f"(d[107]), "+f"(d[108]), "+f"(d[109]), "+f"(d[110]), "+f"(d[111]), "+f"(d[112]), "+f"(d[113]), "+f"(d[114]), "+f"(d[115]), "+f"(d[116]), "+f"(d[117]), "+f"(d[118]), "+f"(d[119]), "+f"(d[120]), "+f"(d[121]), "+f"(d[122]), "+f"(d[123]), "+f"(d[124]), "+f"(d[125]), "+f"(d[126]), "+f"(d[127])
    : "r"(da), "r"(db));
  }
}
template<bool INIT> __device__ __forceinline__ void wgmma_n128_nn(float* d, uint32_t da, uint32_t db) {
  if constexpr (INIT) {
  asm volatile("{\n.reg .pred p;\n.reg .b64 da, db;\nsetp.ne.b32 p, 0, 0;\nmov.b64 da, {%64, 8};\nmov.b64 db, {%65, 8};\nwgmma.mma_async.sync.aligned.m64n128k16.f32.bf16.bf16 {%0, %1, %2, %3, %4, %5, %6, %7, %8, %9, %10, %11, %12, %13, %14, %15, %16, %17, %18, %19, %20, %21, %22, %23, %24, %25, %26, %27, %28, %29, %30, %31, %32, %33, %34, %35, %36, %37, %38, %39, %40, %41, %42, %43, %44, %45, %46, %47, %48, %49, %50, %51, %52, %53, %54, %55, %56, %57, %58, %59, %60, %61, %62, %63}, da, db, p, 1, 1, 0, 0;\n}\n"
    : "=f"(d[0]), "=f"(d[1]), "=f"(d[2]), "=f"(d[3]), "=f"(d[4]), "=f"(d[5]), "=f"(d[6]), "=f"(d[7]), "=f"(d[8]), "=f"(d[9]), "=f"(d[10]), "=f"(d[11]), "=f"(d[12]), "=f"(d[13]), "=f"(d[14]), "=f"(d[15]), "=f"(d[16]), "=f"(d[17]), "=f"(d[18]), "=f"(d[19]), "=f"(d[20]), "=f"(d[21]), "=f"(d[22]), "=f"(d[23]), "=f"(d[24]), "=f"(d[25]), "=f"(d[26]), "=f"(d[27]), "=f"(d[28]), "=f"(d[29]), "=f"(d[30]), "=f"(d[31]), "=f"(d[32]), "=f"(d[33]), "=f"(d[34]), "=f"(d[35]), "=f"(d[36]), "=f"(d[37]), "=f"(d[38]), "=f"(d[39]), "=f"(d[40]), "=f"(d[41]), "=f"(d[42]), "=f"(d[43]), "=f"(d[44]), "=f"(d[45]), "=f"(d[46]), "=f"(d[47]), "=f"(d[48]), "=f"(d[49]), "=f"(d[50]), "=f"(d[51]), "=f"(d[52]), "=f"(d[53]), "=f"(d[54]), "=f"(d[55]), "=f"(d[56]), "=f"(d[57]), "=f"(d[58]), "=f"(d[59]), "=f"(d[60]), "=f"(d[61]), "=f"(d[62]), "=f"(d[63])
    : "r"(da), "r"(db));
  } else {
  asm volatile("{\n.reg .pred p;\n.reg .b64 da, db;\nsetp.ne.b32 p, 1, 0;\nmov.b64 da, {%64, 8};\nmov.b64 db, {%65, 8};\nwgmma.mma_async.sync.aligned.m64n128k16.f32.bf16.bf16 {%0, %1, %2, %3, %4, %5, %6, %7, %8, %9, %10, %11, %12, %13, %14, %15, %16, %17, %18, %19, %20, %21, %22, %23, %24, %25, %26, %27, %28, %29, %30, %31, %32, %33, %34, %35, %36, %37, %38, %39, %40, %41, %42, %43, %44, %45, %46, %47, %48, %49, %50, %51, %52, %53, %54, %55, %56, %57, %58, %59, %60, %61, %62, %63}, da, db, p, 1, 1, 0, 0;\n}\n"
    : "+f"(d[0]), "+f"(d[1]), "+f"(d[2]), "+f"(d[3]), "+f"(d[4]), "+f"(d[5]), "+f"(d[6]), "+f"(d[7]), "+f"(d[8]), "+f"(d[9]), "+f"(d[10]), "+f"(d[11]), "+f"(d[12]), "+f"(d[13]), "+f"(d[14]), "+f"(d[15]), "+f"(d[16]), "+f"(d[17]), "+f"(d[18]), "+f"(d[19]), "+f"(d[20]), "+f"(d[21]), "+f"(d[22]), "+f"(d[23]), "+f"(d[24]), "+f"(d[25]), "+f"(d[26]), "+f"(d[27]), "+f"(d[28]), "+f"(d[29]), "+f"(d[30]), "+f"(d[31]), "+f"(d[32]), "+f"(d[33]), "+f"(d[34]), "+f"(d[35]), "+f"(d[36]), "+f"(d[37]), "+f"(d[38]), "+f"(d[39]), "+f"(d[40]), "+f"(d[41]), "+f"(d[42]), "+f"(d[43]), "+f"(d[44]), "+f"(d[45]), "+f"(d[46]), "+f"(d[47]), "+f"(d[48]), "+f"(d[49]), "+f"(d[50]), "+f"(d[51]), "+f"(d[52]), "+f"(d[53]), "+f"(d[54]), "+f"(d[55]), "+f"(d[56]), "+f"(d[57]), "+f"(d[58]), "+f"(d[59]), "+f"(d[60]), "+f"(d[61]), "+f"(d[62]), "+f"(d[63])
    : "r"(da), "r"(db));
  }
}
template<bool INIT> __device__ __forceinline__ void wgmma_n64_tt(float* d, uint32_t da, uint32_t db) {
  if constexpr (INIT) {
  asm volatile("{\n.reg .pred p;\n.reg .b64 da, db;\nsetp.ne.b32 p, 0, 0;\nmov.b64 da, {%32, 0x40000040};\nmov.b64 db, {%33, 0x40000040};\nwgmma.mma_async.sync.aligned.m64n64k16.f32.bf16.bf16 {%0, %1, %2, %3, %4, %5, %6, %7, %8, %9, %10, %11, %12, %13, %14, %15, %16, %17, %18, %19, %20, %21, %22, %23, %24, %25, %26, %27, %28, %29, %30, %31}, da, db, p, 1, 1, 1, 1;\n}\n"
    : "=f"(d[0]), "=f"(d[1]), "=f"(d[2]), "=f"(d[3]), "=f"(d[4]), "=f"(d[5]), "=f"(d[6]), "=f"(d[7]), "=f"(d[8]), "=f"(d[9]), "=f"(d[10]), "=f"(d[11]), "=f"(d[12]), "=f"(d[13]), "=f"(d[14]), "=f"(d[15]), "=f"(d[16]), "=f"(d[17]), "=f"(d[18]), "=f"(d[19]), "=f"(d[20]), "=f"(d[21]), "=f"(d[22]), "=f"(d[23]), "=f"(d[24]), "=f"(d[25]), "=f"(d[26]), "=f"(d[27]), "=f"(d[28]), "=f"(d[29]), "=f"(d[30]), "=f"(d[31])
    : "r"(da), "r"(db));
  } else {
  asm volatile("{\n.reg .pred p;\n.reg .b64 da, db;\nsetp.ne.b32 p, 1, 0;\nmov.b64 da, {%32, 0x40000040};\nmov.b64 db, {%33, 0x40000040};\nwgmma.mma_async.sync.aligned.m64n64k16.f32.bf16.bf16 {%0, %1, %2, %3, %4, %5, %6, %7, %8, %9, %10, %11, %12, %13, %14, %15, %16, %17, %18, %19, %20, %21, %22, %23, %24, %25, %26, %27, %28, %29, %30, %31}, da, db, p, 1, 1, 1, 1;\n}\n"
    : "+f"(d[0]), "+f"(d[1]), "+f"(d[2]), "+f"(d[3]), "+f"(d[4]), "+f"(d[5]), "+f"(d[6]), "+f"(d[7]), "+f"(d[8]), "+f"(d[9]), "+f"(d[10]), "+f"(d[11]), "+f"(d[12]), "+f"(d[13]), "+f"(d[14]), "+f"(d[15]), "+f"(d[16]), "+f"(d[17]), "+f"(d[18]), "+f"(d[19]), "+f"(d[20]), "+f"(d[21]), "+f"(d[22]), "+f"(d[23]), "+f"(d[24]), "+f"(d[25]), "+f"(d[26]), "+f"(d[27]), "+f"(d[28]), "+f"(d[29]), "+f"(d[30]), "+f"(d[31])
    : "r"(da), "r"(db));
  }
}
template<bool INIT> __device__ __forceinline__ void wgmma_n8_tn(float* d, uint32_t da, uint32_t db) {
  if constexpr (INIT) {
  asm volatile("{\n.reg .pred p;\n.reg .b64 da, db;\nsetp.ne.b32 p, 0, 0;\nmov.b64 da, {%4, 0x40000040};\nmov.b64 db, {%5, 8};\nwgmma.mma_async.sync.aligned.m64n8k16.f32.bf16.bf16 {%0, %1, %2, %3}, da, db, p, 1, 1, 1, 0;\n}\n"
    : "=f"(d[0]), "=f"(d[1]), "=f"(d[2]), "=f"(d[3])
    : "r"(da), "r"(db));
  } else {
  asm volatile("{\n.reg .pred p;\n.reg .b64 da, db;\nsetp.ne.b32 p, 1, 0;\nmov.b64 da, {%4, 0x40000040};\nmov.b64 db, {%5, 8};\nwgmma.mma_async.sync.aligned.m64n8k16.f32.bf16.bf16 {%0, %1, %2, %3}, da, db, p, 1, 1, 1, 0;\n}\n"
    : "+f"(d[0]), "+f"(d[1]), "+f"(d[2]), "+f"(d[3])
    : "r"(da), "r"(db));
  }
}
template<bool INIT> __device__ __forceinline__ void wgmma_n40_tf32(float* d, const uint32_t* a, uint32_t db) {
  if constexpr (INIT) {
  asm volatile("{\n.reg .pred p;\n.reg .b64 db;\nsetp.ne.b32 p, 0, 0;\nmov.b64 db, {%24, 0x40000040};\nwgmma.mma_async.sync.aligned.m64n40k8.f32.tf32.tf32 {%0, %1, %2, %3, %4, %5, %6, %7, %8, %9, %10, %11, %12, %13, %14, %15, %16, %17, %18, %19}, {%20, %21, %22, %23}, db, p, 1, 1;\n}\n"
    : "=f"(d[0]), "=f"(d[1]), "=f"(d[2]), "=f"(d[3]), "=f"(d[4]), "=f"(d[5]), "=f"(d[6]), "=f"(d[7]), "=f"(d[8]), "=f"(d[9]), "=f"(d[10]), "=f"(d[11]), "=f"(d[12]), "=f"(d[13]), "=f"(d[14]), "=f"(d[15]), "=f"(d[16]), "=f"(d[17]), "=f"(d[18]), "=f"(d[19])
    : "r"(a[0]), "r"(a[1]), "r"(a[2]), "r"(a[3]), "r"(db));
  } else {
  asm volatile("{\n.reg .pred p;\n.reg .b64 db;\nsetp.ne.b32 p, 1, 0;\nmov.b64 db, {%24, 0x40000040};\nwgmma.mma_async.sync.aligned.m64n40k8.f32.tf32.tf32 {%0, %1, %2, %3, %4, %5, %6, %7, %8, %9, %10, %11, %12, %13, %14, %15, %16, %17, %18, %19}, {%20, %21, %22, %23}, db, p, 1, 1;\n}\n"
    : "+f"(d[0]), "+f"(d[1]), "+f"(d[2]), "+f"(d[3]), "+f"(d[4]), "+f"(d[5]), "+f"(d[6]), "+f"(d[7]), "+f"(d[8]), "+f"(d[9]), "+f"(d[10]), "+f"(d[11]), "+f"(d[12]), "+f"(d[13]), "+f"(d[14]), "+f"(d[15]), "+f"(d[16]), "+f"(d[17]), "+f"(d[18]), "+f"(d[19])
    : "r"(a[0]), "r"(a[1]), "r"(a[2]), "r"(a[3]), "r"(db));
  }
}

__device__ __forceinline__ void quad_transpose(uint32_t& r0, uint32_t& r1, uint32_t& r2, uint32_t& r3, int c) {
  bool o1 = c & 1, o2 = c & 2;
  uint32_t t0 = o1 ? r0 : r1, t1 = o1 ? r2 : r3;
  t0 = __shfl_xor_sync(~0u, t0, 1); t1 = __shfl_xor_sync(~0u, t1, 1);
  if (o1) { r0 = t0; r2 = t1; } else { r1 = t0; r3 = t1; }
  t0 = o2 ? r0 : r2; t1 = o2 ? r1 : r3;
  t0 = __shfl_xor_sync(~0u, t0, 2); t1 = __shfl_xor_sync(~0u, t1, 2);
  if (o2) { r0 = t0; r1 = t1; } else { r2 = t0; r3 = t1; }
}

__device__ __forceinline__ bool own_tile(int T) { return (0x0D0Cu >> T) & 1; }
__device__ __forceinline__ bool wide_tile(int T) { return (0x3939u >> T) & 1; }

template<int V> struct IntC { static constexpr int value = V; };

__device__ __forceinline__ const CUtensorMap* tile_info(const Params& prm, int T, int j, int rank, int& col) {
  const int tile = T & 7;
  col = 128 * j + 64 * rank;
  if (tile == 0) col = 1024 + 1024 * rank + 128 * j;
  if (tile < 2) return T < 8 ? &prm.wqkv_n : &prm.wqkv_p;
  if (tile == 2) return &prm.wo_p;
  if (tile == 7) return &prm.wd_p;
  col = 448 * j + 128 * (tile - 3);
  return rank ? &prm.wu_p : &prm.wg_p;
}

__device__ __forceinline__ void split3(float x, uint32_t& a, uint32_t& b, uint32_t& c) {
  a = pack_bf16(0.f, x); x -= __uint_as_float(a);
  b = pack_bf16(0.f, x); x -= __uint_as_float(b);
  c = pack_bf16(0.f, x);
}
__device__ __forceinline__ void tile_stats(const uint32_t* P, float2 (*st)[8], int row, int j, int lane) {
  float s[2][4] = {}, q[2][2][4] = {};
#pragma unroll
  for (int i = 0; i < 8; i++) {
    const uint32_t* p = P + 4 * i;
    float* d = s[i & 1];
    asm("mma.sync.aligned.m16n8k16.row.col.f32.bf16.bf16.f32 {%0, %1, %2, %3}, {%4, %5, %6, %7}, {%8, %8}, {%0, %1, %2, %3};"
        : "+f"(d[0]), "+f"(d[1]), "+f"(d[2]), "+f"(d[3]) : "r"(p[0]), "r"(p[1]), "r"(p[2]), "r"(p[3]), "r"(0x3F803F80u));
#pragma unroll
    for (int t = 0; t < 4; t++) {
      float* e = q[i & 1][t & 1];
      asm("mma.sync.aligned.m16n8k8.row.col.f32.bf16.bf16.f32 {%0, %1, %2, %3}, {%4, %5}, {%6}, {%0, %1, %2, %3};"
          : "+f"(e[0]), "+f"(e[1]), "+f"(e[2]), "+f"(e[3]) : "r"(p[t & 2]), "r"(p[(t & 2) + 1]), "r"(p[t]));
    }
  }
  const bool odd = lane & 4, diag = (lane & 3) == (lane >> 3);
#pragma unroll
  for (int hf = 0; hf < 2; hf++) {
    const float sum = s[hf][0] + s[hf][2], sq = odd ? q[hf][0][1] + q[hf][1][3] : q[hf][0][0] + q[hf][1][2];
    st_f2_if(&st[row + 8 * hf][j], sum * (1.f / 128.f), fmaxf(sq - sum * sum * (1.f / 128.f), 0.f), diag);
  }
}

__device__ __forceinline__ void pack_half(const float* acc, uint32_t* PK) {
#pragma unroll
  for (int b = 0; b < 16; b++) {
    const int o = ((b >> 2) & 1) * 16 + (b >> 3) * 4 + (b & 3);
    PK[o] = pack_bf16(acc[4 * b], acc[4 * b + 1]);
    PK[o + 8] = pack_bf16(acc[4 * b + 2], acc[4 * b + 3]);
  }
}
template<int N> __device__ __forceinline__ void move_down(uint32_t* PK) {
#pragma unroll
  for (int q = 0; q < N; q++) asm volatile("mov.b32 %0, %1;" : "=r"(PK[q]) : "r"(PK[q + N]));
}
__device__ __forceinline__ void next_unit(uint32_t* PK, int u) {
  if (!(u & 1)) move_down<8>(PK); else if (!(u & 2)) move_down<16>(PK); else move_down<32>(PK);
}
__device__ __forceinline__ void lds_v4(uint32_t* v, uint32_t addr) {
  asm volatile("ld.shared.v4.u32 {%0, %1, %2, %3}, [%4];" : "=r"(v[0]), "=r"(v[1]), "=r"(v[2]), "=r"(v[3]) : "r"(addr) : "memory");
}
__device__ __forceinline__ void lds_tile(uint32_t* P, uint32_t b0, uint32_t b1, uint32_t ioff) {
#pragma unroll
  for (int q = 0; q < 8; q++) lds_v4(P + 4 * q, ((q >> 2) ? b1 : b0) + (q & 1) * 1024 + (ioff ^ ((q & 2) * 32)));
}
__device__ __forceinline__ void transpose_all(uint32_t* P, int c) {
#pragma unroll
  for (int q = 0; q < 8; q++) quad_transpose(P[4 * q], P[4 * q + 1], P[4 * q + 2], P[4 * q + 3], c);
}
__device__ __forceinline__ void add_residual(uint32_t* P, const float* acc) {
#pragma unroll
  for (int b = 0; b < 16; b++) {
    uint32_t& r0 = P[(b >> 2) * 8 + (b & 3)]; uint32_t& r1 = P[(b >> 2) * 8 + 4 + (b & 3)];
    r0 = hadd2(r0, pack_bf16(acc[4 * b], acc[4 * b + 1]));
    r1 = hadd2(r1, pack_bf16(acc[4 * b + 2], acc[4 * b + 3]));
  }
}
__device__ __forceinline__ float phi_s(float raw, float rstd, float rl2) { return fmaxf(fmaf(raw, rstd, 1.000001f), __saturatef(ex2f(raw * rl2) + 1e-6f)); }

template<bool HELPER>
__device__ __forceinline__ void colsum_warp(const Params& prm, uint32_t sb, uint32_t cbar, int id, int m, int j, int lane, uint32_t epoch) {
  const bool lead = elect_one();
  const int nbox = HELPER ? (id < 16 ? 48 : 40) : 2;
  float acc[8] = {};
  auto unit = [&](int b, int& col, int& kb, int& mat) {
    const int un = (b >> 3) * 48 + id, ch = un >> 1;
    kb = (un & 1) * 8 + (b & 7);
    if (ch < 16) col = ch * 64;
    else { const int q = ch - 16; mat = 1 + (q & 1); col = q < 96 ? 448 * ((q >> 2) & 7) + 128 * (q >> 5) + 32 * (q & 2) : 448 * ((q - 96) >> 1) + 384; }
  };
#pragma unroll 1
  for (int it = 0; it < 2 * nbox + 1; it++) {
    const int bx = it >> 1, k = it == 0 ? 0 : 1 - (it & 1);
    const int b = it == 0 ? 0 : k ? bx - 1 : bx + 1;
    if (b >= nbox) continue;
    int col, kb = m, mat = 0;
    if (HELPER) {
      unit(b, col, kb, mat);
    } else {
      col = 1024 + id * 1024 + 128 * j + b * 64;
    }
    const uint32_t sl = b & 1;
    if (k == 0) {
      if (lead) {
        mbar_expect_tx(cbar + 8 * sl, 8192);
        tma_5d(sb + sl * 8192, mat == 0 ? &prm.wqkv_n : mat == 1 ? &prm.wg_p : &prm.wu_p, cbar + 8 * sl, col, kb * 2);
      }
    } else {
      mbar_wait(cbar + 8 * sl, (b >> 1) & 1);
      const uint32_t ad = sb + sl * 8192 + (lane >> 3) * 128;
#pragma unroll 2
      for (int q = 0; q < 8; q++) {
        uint4 v, w;
        asm volatile("ld.shared.v4.u32 {%0, %1, %2, %3}, [%4];" : "=r"(v.x), "=r"(v.y), "=r"(v.z), "=r"(v.w) : "r"(ad + q * 1024 + (((lane & 7) ^ (lane >> 3)) << 4)) : "memory");
        asm volatile("ld.shared.v4.u32 {%0, %1, %2, %3}, [%4];" : "=r"(w.x), "=r"(w.y), "=r"(w.z), "=r"(w.w) : "r"(ad + q * 1024 + 512 + (((lane & 7) ^ (lane >> 3) ^ 4) << 4)) : "memory");
        acc[0] += bf_lo(v.x) + bf_lo(w.x); acc[1] += bf_hi(v.x) + bf_hi(w.x); acc[2] += bf_lo(v.y) + bf_lo(w.y); acc[3] += bf_hi(v.y) + bf_hi(w.y);
        acc[4] += bf_lo(v.z) + bf_lo(w.z); acc[5] += bf_hi(v.z) + bf_hi(w.z); acc[6] += bf_lo(v.w) + bf_lo(w.w); acc[7] += bf_hi(v.w) + bf_hi(w.w);
      }
      __syncwarp();
      if (!HELPER || (b & 7) == 7) {
#pragma unroll
        for (int q = 0; q < 8; q++) { acc[q] += __shfl_xor_sync(~0u, acc[q], 8); acc[q] += __shfl_xor_sync(~0u, acc[q], 16); }
        float* dst = &prm.sc->cs[epoch & 1][(mat == 0 ? 0 : mat == 1 ? 3072 : 3072 + F_) + col + 8 * (lane & 7)];
        if (lane < 8) { red_add_v4(dst, acc[0], acc[1], acc[2], acc[3]); red_add_v4(dst + 4, acc[4], acc[5], acc[6], acc[7]); }
#pragma unroll
        for (int q = 0; q < 8; q++) acc[q] = 0.f;
        if (b == nbox - 1 || (HELPER && (b < 16 || b == 31))) {
          __syncwarp();
          if (lead) { fence_gpu(); red_add_u32(&prm.sc->cscnt[HELPER ? (b > 31 ? 11 : 8 + ((b + 1) >> 4)) : j][0], 1); }
        }
      }
    }
  }
}

#define TR(i)

__global__ void __launch_bounds__(384, 1) fused_kernel(const __grid_constant__ Params prm) {
  extern __shared__ __align__(1024) uint8_t smem_raw[];
#define SMEM_ADDRS \
const uint32_t sbase = __shfl_sync(~0u, smem_u32(smem_raw), 0); \
  const uint32_t full = sbase + OFF_BAR, empty = full + 64; \
  const uint32_t bar_kvdone = full + 128, bar_kvready = full + 136, bar_sig = full + 144; \
  const uint32_t bar_sig2 = full + 160, bar_cs = full + 176, bar_res = full + 216, bar_ln = full + 416;
  const int warp = __shfl_sync(~0u, threadIdx.x >> 5, 0);
  const bool helper = prm.role[blockIdx.x >> 1] >= 64;
#define ROLE_IDS \
  int bid; asm volatile("mov.u32 %0, %%ctaid.x;" : "=r"(bid)); \
  const int rank = bid & 1, role = prm.role[bid >> 1], mp = role & 7, j = role >> 3; \
  const int m = mp * 2 + rank, cta = m * 8 + j;

  {
  SMEM_ADDRS
  ROLE_IDS
  if (elect_one()) {
    if (!helper) {
      const int q = m >> 2, kb = 2 * ((q >> 1) + ((q >> 1) >= j)) + (q & 1);
      if (warp == 1) asm volatile("cp.async.bulk.prefetch.tensor.2d.L2.global.tile [%0, {%1, %2}];" :: "l"((uint64_t)&prm.x), "r"(j * 64), "r"(m * 128) : "memory");
      if (warp == 0) tma_5d_prefetch(&prm.wqkv_n, 1024 + 1024 * rank + 128 * j + (m & 2) * 32, kb * 2);
    }
#pragma unroll 1
    for (int t = warp; t < 53; t += 12) mbar_init(full + 8 * t, t < 8 ? 1 : t < 16 ? 4 : t == 16 ? 8 : (t >= 18 && t < 22) ? 4 : 1);
    asm volatile("fence.mbarrier_init.release.cluster;" ::: "memory");
  }
  }
  __syncwarp();
  asm volatile("barrier.cluster.arrive.relaxed.aligned;" ::: "memory");

  if (helper) {
    SMEM_ADDRS
    cluster_wait();
    colsum_warp<true>(prm, sbase + warp * 16384, full + 224 + warp * 16, (blockIdx.x & 3) * 12 + warp, 0, 0, lane_id(), load_epoch());
  } else if (warp >= 4) {
    asm volatile("setmaxnreg.inc.sync.aligned.u32 232;");
    SMEM_ADDRS
    ROLE_IDS
    const int lane = lane_id();
    const int cw = (warp >> 2) - 1, w4 = warp & 3, g = lane >> 2, c = lane & 3;
    uint32_t PK[64];
    const uint32_t xoff = ((m * 128 + cw * 64 + w4 * 16 + g) * D_ + 128 * j + 8 * c) * 2;
    if (w4 < 2) sts_u32(sbase + OFF_ONES + (w4 * 32 + lane) * 4, 0x3F803F80u);
    cluster_wait();

    const bool relt = w4 == 0 && lane < 2;
    const uint32_t dones = make_desc(sbase + OFF_ONES, 128);
    {
      const int rloc = cw * 64 + w4 * 16 + g;
      const uint32_t ioff = rloc * 128 + ((c ^ g) << 4);
      const uint32_t da0 = make_desc(sbase + cw * 8192, 16), db0 = make_desc(sbase + SLOT, 8192);
      const uint32_t stg = sbase + OFF_STG + cw * 16384;
      const uint32_t rempty = mapa(empty, lane & 1);
      uint32_t n = 0, pos = 0;
      bool ok = false;
      float rstd0, rstd1;
      TR(0);
#pragma unroll 1
      for (int T = 0; T < 16; T++) {
        const int layer = T >> 3, tile = T & 7;
        const bool wide = wide_tile(T), own = own_tile(T);
        const int nsteps = tile == 7 ? 56 : 16;
        const bool lnin = tile == 0 || tile == 3;
        float2 (*st)[8] = prm.sc->rb[m].stats[layer * 2 + (tile != 0)];
        if (tile == 3) { pos += 2048; if (pos >= NSLOT * 1024) pos -= NSLOT * 1024; }
        auto run = [&](auto WIDE_) {
          constexpr bool WIDE = decltype(WIDE_)::value;
          float acc[WIDE ? 128 : 64];
          auto kstep = [&](auto FIRST_, auto&& hook) {
            constexpr bool FIRST = decltype(FIRST_)::value;
            if (!ok) mbar_wait(full + 8 * (n & 7), (n >> 3) & 1);
            const uint32_t da = da0 + pos, db = db0 + pos;
            n++;
            pos += WIDE ? 3072 : 2048; if (pos >= NSLOT * 1024) pos -= NSLOT * 1024;
            KFENCE;
#pragma unroll
            for (int kk = 0; kk < 4; kk++) {
              if (FIRST && kk == 0) { if constexpr (WIDE) wgmma_n256_ss<true>(acc, da, db); else wgmma_n128_ss<true>(acc, da, db); }
              else { if constexpr (WIDE) wgmma_n256_ss<false>(acc, da + kk * 2, db + kk * 128); else wgmma_n128_ss<false>(acc, da + kk * 2, db + kk * 128); }
              if (kk == 1) {
                if constexpr (!FIRST) {
                  wgmma_commit();
                  wgmma_wait<1>();
                  mbar_arrive_remote_if(rempty + 8 * ((n - 2) & 7), relt);
                }
                ok = mbar_test(full + 8 * (n & 7), (n >> 3) & 1);
              }
              if (kk == 3) wgmma_commit();
              hook(kk);
            }
          };
          auto nohook = [](int) {};
          uint8_t* img = prm.sc->rb[m].act[WIDE ? (tile == 0 ? 2 : 1) : 0] + 2 * j * SLOT;
          if (own) {
#pragma unroll
            for (int q = WIDE ? 0 : 4; q < (WIDE ? 4 : 8); q++)
              *(uint4*)(img + (q >> 2) * SLOT + (q & 1) * 1024 + (ioff ^ ((q & 2) * 32))) = make_uint4(PK[4 * q], PK[4 * q + 1], PK[4 * q + 2], PK[4 * q + 3]);
            __syncwarp();
            mbar_arrive_if((WIDE ? bar_sig : bar_sig2) + 8 * cw, lane == 0);
            mbar_wait(full + 8 * (n & 7), (n >> 3) & 1);
            if (WIDE) tile_stats(PK, st, rloc, j, lane);
            mbar_wait(full + 8 * ((n + 1) & 7), ((n + 1) >> 3) & 1);
            ok = true;
            uint32_t p1 = pos + (WIDE ? 3072 : 2048); if (p1 >= NSLOT * 1024) p1 -= NSLOT * 1024;
#pragma unroll
            for (int q = 0; q < 8; q++)
              sts_v4(sbase + ((q >> 2) ? p1 : pos) * 16 + (q & 1) * 1024 + (ioff ^ ((q & 2) * 32)), make_uint4(PK[4 * q], PK[4 * q + 1], PK[4 * q + 2], PK[4 * q + 3]));
            fence_async_smem();
            wg_bar(1 + cw);
          }
          kstep(IntC<1>{}, nohook);
          int i = 1;
          {
            if (tile >= 4) {
              uint32_t* t = PK;
              const int nu = tile == 6 ? 4 : 8;
              uint8_t* hb = prm.sc->rb[m].h + ((tile - 4) * 16 + (tile == 7 ? j : 2 * j)) * SLOT;
              const int hb2 = tile == 7 ? (j - 15) * (int)SLOT : SLOT;
#pragma unroll 1
              for (int u = 0; u < nu; u++) {
                const float rstd = (u & 1) ? rstd1 : rstd0;
                const float ke = rstd * -1.4426950408889634f, iv = rcpf(rstd * rstd);
                auto glu = [&](int q) {
                  float s0 = rcpf(fmaf(ex2f(bf_lo(t[q]) * ke), iv, iv)), s1 = rcpf(fmaf(ex2f(bf_hi(t[q]) * ke), iv, iv));
                  t[q] = hmul2(hmul2(t[q], t[4 + q]), pack_bf16(s0, s1));
                };
                if constexpr (WIDE) kstep(IntC<0>{}, glu);
                else {
                  kstep(IntC<0>{}, [&](int q) { if (q & 1) glu(q >> 1); });
                  kstep(IntC<0>{}, [&](int q) { if (q & 1) glu(2 + (q >> 1)); });
                  i++;
                }
                *(uint4*)(hb + (u >> 2) * hb2 + (u & 1) * 1024 + (ioff ^ ((u & 2) * 32))) = make_uint4(t[0], t[1], t[2], t[3]);
                next_unit(PK, u);
                i++;
              }
              __syncwarp();
              mbar_arrive_if(bar_sig + 8 * cw, lane == 0);
            }
          }
          int stop = tile == 7 ? 24 + RSK * cw : T ? 2 : 5;
#pragma unroll 1
          for (int seg = 0; seg < 3; seg++) {
#pragma unroll 1
            for (; i < stop; i++) kstep(IntC<0>{}, nohook);
            if (seg == 0) {
              if (!WIDE && (tile == 2 || tile == 7)) {
                mbar_wait(bar_res, tile & 1);
                lds_tile(PK, sbase + OFF_STG, sbase + OFF_STG + SLOT, ioff);
                if (T == 2) transpose_all(PK, c);
              }
              if (WIDE && own) {
#pragma unroll
                for (int q = 4; q < 8; q++)
                  *(uint4*)(img + SLOT + (q & 1) * 1024 + (ioff ^ ((q & 2) * 32))) = make_uint4(PK[4 * q], PK[4 * q + 1], PK[4 * q + 2], PK[4 * q + 3]);
              }
              if (WIDE && lnin) {
                if (T == 0) {
                  mbar_wait(full + 40, 0); lds_tile(PK, sbase, sbase + 3 * SLOT, ioff);
                  tile_stats(PK, st, rloc, j, lane);
                }
                __syncwarp();
                mbar_arrive_if(bar_sig2 + 8 * cw, lane == 0);
              }
              stop = nsteps - (WIDE ? SKW : SKN);
            } else {
              if (seg == 1) {
                if (WIDE && lnin) {
                  mbar_wait(bar_ln, tile != 0);
                  const uint32_t r0 = lds_u32(sbase + OFF_LN + rloc * 16 + 12), r1 = lds_u32(sbase + OFF_LN + rloc * 16 + 140);
                  rstd0 = bf_lo(r0) + bf_hi(r0); rstd1 = bf_lo(r1) + bf_hi(r1);
                }
                if (WIDE || tile == 1) mbar_wait(bar_cs + 8 * (tile - (tile > 2)), layer);
              }
              if (HS && seg == 1 && cw == 1) asm volatile("bar.sync 3, 256;" ::: "memory");
              stop = nsteps;
            }
          }
          if (WIDE || tile == 1 || tile == 6) {
            const uint32_t dc = make_desc(sbase + (tile == 0 ? OFF_CSKV : tile == 1 ? OFF_CSQ : OFF_CSGU + (tile - 3) * 4096), 0);
            wgmma_fence();
            if constexpr (WIDE) wgmma_n256_nn<false>(acc, make_desc(sbase + OFF_LN + cw * 1024, 0), dc); else wgmma_n128_nn<false>(acc, make_desc(sbase + OFF_LN + cw * 1024, 0), dc);
            wgmma_commit();
          }
          if (HS && cw == 0) asm volatile("bar.arrive 3, 256;" ::: "memory");
        wgmma_wait<0>();
        mbar_arrive_remote_if(rempty + 8 * ((n - 1) & 7), relt);
        TR(1 + 2 * T);
        if (!WIDE && (tile == 2 || tile == 7)) add_residual(PK, acc);
        else if (WIDE && tile == 0) {
          const float l0 = rstd0 * 1.4426950408889634f, l1 = rstd1 * 1.4426950408889634f;
          const uint32_t sta = stg + (w4 * 16 + ((lane >> 3) & 1) * 8 + (lane & 7)) * 128, da = make_desc(stg, 8192);
          float kv[2][32], z[2][4];
          if (cw == 0) asm volatile("bar.arrive 4, 256;" ::: "memory");
#pragma unroll
          for (int r = 0; r < 2; r++) {
            uint32_t* t = PK + 32 * r;
#pragma unroll
            for (int b = 0; b < 16; b++) {
              const float* a = acc + (WIDE ? 64 * r : 0) + 4 * b;
              const float v0 = a[0], v1 = a[1], v2 = a[2], v3 = a[3];
              if (b < 8) { t[2 * b] = pack_bf16(phi_s(v0, rstd0, l0), phi_s(v1, rstd0, l0)); t[2 * b + 1] = pack_bf16(phi_s(v2, rstd1, l1), phi_s(v3, rstd1, l1)); }
              else { t[2 * b] = pack_bf16(v0 * rstd0, v1 * rstd0); t[2 * b + 1] = pack_bf16(v2 * rstd1, v3 * rstd1); }
            }
            if (r) { wgmma_wait<0>(); wg_bar(1 + cw); }
            else if (cw == 1) asm volatile("bar.sync 4, 256;" ::: "memory");
#pragma unroll
            for (int b = 0; b < 16; b += 2)
              stmatrix_x4(sta + (b >> 3) * 8192 + ((((b & 7) + (lane >> 4)) ^ (lane & 7)) << 4), t[2 * b], t[2 * b + 1], t[2 * b + 2], t[2 * b + 3]);
            fence_async_smem();
            wg_bar(1 + cw);
            wgmma_fence();
            wgmma_n64_tt<true>(kv[r], da + 512, da);
            wgmma_n8_tn<true>(z[r], da, dones);
#pragma unroll
            for (int kk = 1; kk < 4; kk++) {
              wgmma_n64_tt<false>(kv[r], da + 512 + kk * 128, da + kk * 128);
              wgmma_n8_tn<false>(z[r], da + kk * 128, dones);
            }
            wgmma_commit();
          }
          wgmma_wait<0>();
          wg_bar(1 + cw);
          const uint32_t kb = stg + (w4 * 16 + g) * 128 + c * 4;
          float* zd = &prm.sc->kv[lds_u32(full + 480) & 1][layer][j][4096 + (w4 >> 1) * 32 + (w4 & 1) * 16 + (g & 1) * 4 + (g >> 1)];
#pragma unroll
          for (int r = 0; r < 2; r++) {
#pragma unroll
            for (int q = 0; q < 16; q++)
              sts_u32(kb + r * 8192 + (q & 2) * 512 + ((((q >> 2) * 2 + (q & 1)) ^ g) << 4), __float_as_uint(w4 >= 2 ? kv[r][16 + q] : kv[r][q]));
            red_add_f32_if(zd + 64 * r, z[r][0], c == 0); red_add_f32_if(zd + 64 * r + 8, z[r][2], c == 0);
          }
          fence_async_smem();
          __syncwarp();
          mbar_arrive_if(bar_kvdone, lane == 0);
        } else if (WIDE || tile != 1) {
          pack_half(acc, PK);
          if constexpr (WIDE) pack_half(acc + 64, PK + 32);
        } else {
          const float l0 = rstd0 * 1.4426950408889634f, l1 = rstd1 * 1.4426950408889634f;
#pragma unroll
          for (int hp = 0; hp < 2; hp++) {
            uint32_t* A = PK + 32;
#pragma unroll
            for (int b = 0; b < 8; b++) {
              const float* a = acc + 32 * hp + 4 * b;
              A[4 * b] = __float_as_uint(phi_s(a[0], rstd0, l0));
              A[4 * b + 1] = __float_as_uint(phi_s(a[2], rstd1, l1));
              A[4 * b + 2] = __float_as_uint(phi_s(a[1], rstd0, l0));
              A[4 * b + 3] = __float_as_uint(phi_s(a[3], rstd1, l1));
            }
            mbar_wait(bar_kvready, layer);
            float num[2][20];
            wgmma_fence();
#pragma unroll
            for (int ks = 0; ks < 4; ks++) {
#pragma unroll
              for (int hh = 0; hh < 2; hh++) {
                const uint32_t db = make_desc(sbase + OFF_STG + (2 * hp + hh) * 5120, 16) + 2 * ks;
                if (ks == 0) wgmma_n40_tf32<true>(num[hh], A + 16 * hh, db); else wgmma_n40_tf32<false>(num[hh], A + 16 * hh + 4 * ks, db);
              }
            }
            wgmma_commit();
            wgmma_wait<0>();
#pragma unroll
            for (int hh = 0; hh < 2; hh++) {
              const float* nm = num[hh];
              const float r0 = rcpf(__shfl_sync(~0u, nm[16], 0, 4) + 1e-6f), r1 = rcpf(__shfl_sync(~0u, nm[18], 0, 4) + 1e-6f);
#pragma unroll
              for (int b = 0; b < 4; b++) {
                PK[16 * hp + 8 * hh + b] = pack_bf16(nm[4 * b] * r0, nm[4 * b + 1] * r0);
                PK[16 * hp + 8 * hh + 4 + b] = pack_bf16(nm[4 * b + 2] * r1, nm[4 * b + 3] * r1);
              }
            }
            if (hp == 0) {
#pragma unroll
              for (int q = 0; q < 4; q++)
                *(uint4*)(img + (q & 1) * 1024 + (ioff ^ ((q & 2) * 32))) = make_uint4(PK[4 * q], PK[4 * q + 1], PK[4 * q + 2], PK[4 * q + 3]);
              __syncwarp();
              mbar_arrive_if(bar_sig + 8 * cw, lane == 0);
              mbar_wait(bar_kvready, layer);
            }
          }
        }
        };
        if (wide) run(IntC<1>{}); else run(IntC<0>{});
        TR(2 + 2 * T);
      }
      asm volatile("barrier.cluster.arrive.relaxed.aligned;" ::: "memory");
      transpose_all(PK, c);
#pragma unroll
      for (int q = 0; q < 8; q++)
        *(uint4*)((uint8_t*)prm.out + xoff + (q >> 1) * 64 + (q & 1) * 16 * D_) = make_uint4(PK[4 * q], PK[4 * q + 1], PK[4 * q + 2], PK[4 * q + 3]);
      if (cta == 0 && threadIdx.x == 128) prm.sc->epoch = lds_u32(full + 480);
    }
  } else {
    asm volatile("setmaxnreg.dec.sync.aligned.u32 40;");
    SMEM_ADDRS
    const int lane = lane_id();
    if (__builtin_expect(warp < 2, 1)) {
      ROLE_IDS
      uint32_t epoch = 0;
      auto border = [&](int T, int i) {
        if (own_tile(T)) { const int e = i > 8, q = i - 2 - 7 * e; return i < 2 ? 2 * j + i : 2 * (q + (q >= j)) + e; }
        if (T == 0) { const int p = i >> 1, q = p - (p > 2); return 2 * (p == 2 ? j : q + (q >= j)) + (i & 1); }
        return i;
      };
      if (warp == 0) {
        uint32_t n = 0, dst = sbase + SLOT + rank * 8192;
        const uint32_t dend = dst + NSLOT * SLOT;
        const bool lead = elect_one();
#pragma unroll 1
        for (int T = 0; T < 16; T++) {
          const int tile = T & 7;
          const bool wide = wide_tile(T);
          const uint32_t adv = (wide ? 3 : 2) * SLOT, dfill = wide ? 0x34000000u : 0x56000000u;
          uint32_t dtab = tile == 0 ? 0x34343445u : tile == 3 ? 0x34343334u : wide ? 0x34343434u : (tile == 1 || tile == 6) ? 0x56554534u : 0x56565656u;
          if (tile == 3) { dst += 2 * SLOT; if (dst >= dend) dst -= NSLOT * SLOT; }
          int col;
          const CUtensorMap* map = tile_info(prm, T, j, rank, col);
#pragma unroll 1
          for (int p = 0; p < (tile == 7 ? 28 : 8); p++) {
            int k0, k1;
            if (tile == 7) { k0 = p < 24 ? 7 * (p & 7) + 2 * (p >> 3) : 14 * p - 330; k1 = k0 + (p < 24 ? 1 : 7); }
            else { k0 = border(T, 2 * p); k1 = border(T, 2 * p + 1); }
            const int X0 = n - (dtab & 15), X1 = n - ((dtab >> 4) & 15);
            dtab = (dtab >> 8) | dfill;
            const uint32_t fb = full + 8 * (n & 7), bytes = (own_tile(T) && p == 0) ? adv - SLOT : adv;
            uint32_t dst1 = dst + adv; if (dst1 >= dend) dst1 -= NSLOT * SLOT;
            if (n == 0) cluster_wait();
            if (n >= 4) mbar_wait(empty + 8 * (X0 & 7), (X0 >> 3) & 1);
            if (lead) {
              mbar_expect_tx(fb, bytes);
              tma_5d_mc(dst, map, fb, col, k0 * 2);
              if (wide) tma_5d_mc(dst + SLOT, map, fb, col + 64, k0 * 2);
            }
            if (n >= 4) mbar_wait(empty + 8 * (X1 & 7), (X1 >> 3) & 1);
            if (lead) {
              mbar_expect_tx(fb + 8, bytes);
              tma_5d_mc(dst1, map, fb + 8, col, k1 * 2);
              if (wide) tma_5d_mc(dst1 + SLOT, map, fb + 8, col + 64, k1 * 2);
            }
            n += 2;
            dst = dst1 + adv; if (dst >= dend) dst -= NSLOT * SLOT;
          }
        }
      } else {
        uint32_t ready = 0, n = 0, dst = sbase;
        const uint32_t dend = dst + NSLOT * SLOT;
        const bool lead = elect_one();
        cluster_wait();
#pragma unroll 1
        for (int T = 0; T < 16; T++) {
          const int layer = T >> 3, tile = T & 7;
          const bool wide = wide_tile(T), own = own_tile(T);
          const uint32_t adv = (wide ? 3 : 2) * SLOT, dfill = wide ? 0x40000000u : 0x60000000u;
          uint32_t dtab = tile == 0 ? 0x44444455u : tile == 3 ? 0x44444344u : wide ? 0x44444444u : (tile == 1 || tile == 6) ? 0x66655544u : 0x66666666u;
          if (tile == 3) dst += 2 * SLOT;
          const int kind = tile < 2 ? 3 : tile == 2 ? 0 : tile < 7 ? 1 : 2;
          const uint8_t* img = prm.sc->rb[m].act[0] + (kind ^ (kind >> 1)) * 16 * SLOT;
          const uint32_t* fl = &prm.sc->rb[m].flag[layer][kind][lane];
          if ((0x8Du >> tile) & 1) ready = 0;
          if (T == 1) epoch = load_epoch();
          int i = 0;
          if (own) { i = 2; n += 2; dst += 2 * adv; dtab = (dtab >> 8) | dfill | (dfill >> 4); }
          if (dst >= dend) dst -= NSLOT * SLOT;
          const int ab = border(T, lane);
          if (T < 2) {
#pragma unroll 1
            for (; i < 16; i++) {
              const int X = n - (dtab & 15);
              dtab = (dtab >> 4) | dfill;
              const int c0 = border(T, i) * 64;
              if (X >= 0) mbar_wait(empty + 8 * (X & 7), (X >> 3) & 1);
              if (lead) tma_2d(dst, &prm.x, full + 8 * (n & 7), c0, m * 128);
              n++; dst += adv; if (dst >= dend) dst -= NSLOT * SLOT;
            }
          } else {
            int blk = own ? (j ? 0 : 2) : 0;
            const int inc = own ? 2 : 1, skip = own ? j : -1;
            uint32_t ok = 0;
#pragma unroll 1
            for (; i < (tile == 7 ? 56 : 16); i++) {
              if (!(ok & 1)) {
                const int ii = (i & 32) + lane;
                const uint32_t need = tile == 7 ? (ii < 32 ? 1u << (ii >> 1) : ii < 48 ? 0x101u << (ii >> 1) : 1u << (ii - 24)) : ((ab & 1) ? 256u : 1u) << (ab >> 1);
                uint32_t tries = 0;
                while (!((ok = __ballot_sync(~0u, (ready & need) == need) >> (i & 31)) & 1)) {
                  ready = __ballot_sync(~0u, ld_acquire(fl) == epoch);
                  if (++tries > (1u << 20)) __trap();
                }
                fence_async_global();
              }
              ok >>= 1;
              const int X = n - (dtab & 15);
              dtab = (dtab >> 4) | dfill;
              mbar_wait(empty + 8 * (X & 7), (X >> 3) & 1);
              if (lead) bulk_load(dst, img + blk * SLOT, SLOT, full + 8 * (n & 7));
              blk += inc;
              if (own && blk >= 16) blk = 1;
              if ((blk >> 1) == skip) blk += 2;
              if (own && blk >= 16) blk = 1;
              n++; dst += adv; if (dst >= dend) dst -= NSLOT * SLOT;
            }
          }
        }
      }
    } else {
      const int w = warp - 2;
      ROLE_IDS
      cluster_wait();
      const uint32_t epoch = load_epoch();
      sts_u32(full + 480, epoch);
      mbar_wait(full, 0);
      colsum_warp<false>(prm, sbase + OFF_STG + w * 16384, full + 224 + warp * 16, w, m, j, lane, epoch);
      {
        float* z = &prm.sc->kv[(epoch & 1) ^ 1][0][0][0] + (size_t)cta * 528;
        for (int i = w * 32 + lane; i < 132; i += 64) *(float4*)(z + i * 4) = make_float4(0.f, 0.f, 0.f, 0.f);
        if (w && lane < 20) *(float4*)&prm.sc->cs[(epoch & 1) ^ 1][cta * 80 + lane * 4] = make_float4(0.f, 0.f, 0.f, 0.f);
      }
      if (w == 0) {
        int pf = 1;
        uint32_t sigph = 0;
#pragma unroll 1
        for (int ev = 1; ev < 20; ev++) {
          const int layer = ev >= 10, e = ev - 10 * layer;
          const bool se = e < 6 && (e & 1);
          const uint32_t sb = se ? bar_sig2 : bar_sig, sp = (sigph >> se) & 1;
          const int kind = (0x2222110033ull >> (4 * e)) & 3, sub = (0x3210101010ull >> (4 * e)) & 3;
          uint32_t* f = &prm.sc->rb[m].flag[layer][kind][sub * 8 + j];
          mbar_wait(sb, sp); mbar_wait(sb + 8, sp);
          if ((e == 3 || e == 9) && lane == 0) {
            mbar_expect_tx(bar_res, 2 * SLOT);
            if (ev == 3) { tma_2d(sbase + OFF_STG, &prm.x, bar_res, 128 * j, m * 128); tma_2d(sbase + OFF_STG + SLOT, &prm.x, bar_res, 128 * j + 64, m * 128); }
            else bulk_load(sbase + OFF_STG, prm.sc->rb[m].act[e == 3 ? 2 : 1] + 2 * j * SLOT, 2 * SLOT, bar_res);
          }
          if (lane == 0) { fence_gpu(); st_relaxed(f, epoch); fence_async_global(); }
          sigph ^= 1 + se;
          const int hi = min(16, layer * 8 + (int)((PFTAB >> (4 * e)) & 15));
#pragma unroll 1
          for (; pf < hi; pf++) {
            int col;
            const CUtensorMap* map = tile_info(prm, pf, j, rank, col);
#pragma unroll 1
            for (int kb = mp; kb < ((pf & 7) == 7 ? 56 : 16); kb += 8) {
              if (lane == 0) { tma_5d_prefetch(map, col, kb * 2); if (wide_tile(pf)) tma_5d_prefetch(map, col + 64, kb * 2); }
              __nanosleep(PFSLEEP);
            }
          }
          __syncwarp();
        }
      } else {
#pragma unroll 1
        for (int rr = 0; rr < 10; rr++) {
          const int layer = rr >= 5, r = rr - 5 * layer;
          const bool lnr = r == 0 || r == 2;
          if (r == 2) { mbar_wait(bar_sig2, layer ^ 1); mbar_wait(bar_sig2 + 8, layer ^ 1); }
          if (lnr) { mbar_wait(bar_sig2, layer); mbar_wait(bar_sig2 + 8, layer); }
          if (r == 1) {
            float* kvp = prm.sc->kv[epoch & 1][layer][j];
            mbar_wait(bar_kvdone, layer);
            if (lane == 0) {
              bulk_reduce_f32(kvp, sbase + OFF_STG, 16384);
              bulk_reduce_f32(kvp, sbase + OFF_STG + 16384, 16384);
              asm volatile("cp.async.bulk.commit_group;\ncp.async.bulk.wait_group 0;" ::: "memory");
              fence_gpu();
              red_add_u32(&prm.sc->kvcnt[layer][j][0], 1);
              mbar_expect_tx(bar_kvready, 16896);
            }
            __syncwarp();
          }
          poll_eq(&prm.sc->cscnt[r ? 7 + r : j][0], epoch * (r ? 48 : 32));
          {
            const int q0 = r > 2 ? 4 * r - 8 : 0, nq = (0x64424 >> (4 * r)) & 15;
            const uint32_t cb = full + 224 + 56, tmp = sbase + OFF_STG + 24576;
            fence_async_global();
            if (lane == 0) mbar_expect_tx(cb, nq * 256);
            __syncwarp();
            if (lane < nq) bulk_load(tmp + lane * 256, &prm.sc->cs[epoch & 1][(r == 0 ? 1024 + 128 * j : r == 1 ? 128 * j : 3072 + 448 * j + 32 * q0)
                                                                            + (lane & 1) * (r == 0 ? 1024 : r == 1 ? 64 : F_) + (lane >> 1) * 64], 256, cb);
            mbar_wait(cb, 1 ^ (rr & 1));
            const uint32_t ad = sbase + (r == 0 ? OFF_CSKV : r == 1 ? OFF_CSQ : OFF_CSGU) + q0 * 1024;
#pragma unroll 2
            for (int q = lane; q < 64 * nq; q += 32) {
              uint32_t c1, c2, c3;
              split3(__uint_as_float(lds_u32(tmp + q * 4)), c1, c2, c3);
              sts_v4(ad + q * 16, make_uint4(c2 | (c1 >> 16), c3 | (c1 >> 16), c1 | (c2 >> 16), 0));
            }
          }
          fence_async_smem();
          __syncwarp();
          if (lane == 0) mbar_arrive(bar_cs + 8 * r);
          if (lnr) {
            poll_eq(&prm.sc->rb[m].flag[layer][r ? 1 : 3][8 + (lane & 7)], epoch);
            __syncwarp();
            const uint32_t lb = full + 224 + 48;
            if (lane == 0) {
              fence_async_global();
              mbar_expect_tx(lb, 8192);
              bulk_load(sbase + OFF_STG + 16384, prm.sc->rb[m].stats[layer * 2 + (r >> 1)], 8192, lb);
            }
            mbar_wait(lb, 1 ^ (r >> 1));
#pragma unroll 1
            for (int q = 0; q < 4; q++) {
              float4 t0, t1, t2, t3;
              const uint32_t sp = sbase + OFF_STG + 16384 + (q * 32 + lane) * 64;
              lds_v4((uint32_t*)&t0, sp + ((lane << 3) & 48)); lds_v4((uint32_t*)&t1, sp + (((lane << 3) + 16) & 48));
              lds_v4((uint32_t*)&t2, sp + (((lane << 3) + 32) & 48)); lds_v4((uint32_t*)&t3, sp + (((lane << 3) + 48) & 48));
              const float mean = ((t0.x + t0.z) + (t1.x + t1.z) + (t2.x + t2.z) + (t3.x + t3.z)) * 0.125f;
              auto sq = [&](float v) { return (v - mean) * (v - mean); };
              const float m2 = (t0.y + t0.w) + (t1.y + t1.w) + (t2.y + t2.w) + (t3.y + t3.w)
                             + 128.f * (sq(t0.x) + sq(t0.z) + sq(t1.x) + sq(t1.z) + sq(t2.x) + sq(t2.z) + sq(t3.x) + sq(t3.z));
              uint32_t a1, a2, a3, r1, r2, r3;
              split3(-0.5f * mean, a1, a2, a3);
              split3(rsqrtf(m2 * (1.f / 1024.f) + 1e-5f), r1, r2, r3);
              sts_v4(sbase + OFF_LN + (q * 32 + lane) * 16, make_uint4(a1 | (a1 >> 16), a1 | (a2 >> 16), a3 | (a2 >> 16), r1 | (r2 >> 16)));
            }
            fence_async_smem();
            __syncwarp();
            if (lane == 0) mbar_arrive(bar_ln);
          }
          if (r == 1) {
            float* kvp = prm.sc->kv[epoch & 1][layer][j];
            poll_eq(&prm.sc->kvcnt[layer][j][0], epoch * 16);
            fence_async_global();
            if (lane < 8) bulk_load(sbase + OFF_STG + (lane & 3) * 5120 + (lane >> 2) * 4096, kvp + (lane < 4 ? lane * 1024 : 4096 + (lane & 3) * 32), lane < 4 ? 4096 : 128, bar_kvready);
            __syncwarp();
          }
        }
      }
    }
  }
  __syncwarp();
  if (helper || warp < 4) asm volatile("barrier.cluster.arrive.relaxed.aligned;" ::: "memory");
  cluster_wait();
}

typedef CUresult (*EncodeTiledFn)(CUtensorMap*, CUtensorMapDataType, cuuint32_t, void*, const cuuint64_t*, const cuuint64_t*, const cuuint32_t*, const cuuint32_t*,
                                  CUtensorMapInterleave, CUtensorMapSwizzle, CUtensorMapL2promotion, CUtensorMapFloatOOBfill);

void make_wmap(EncodeTiledFn enc, CUtensorMap* m, const void* ptr, uint64_t rows, uint64_t cols, bool perm) {
  uint64_t rs = cols * 2;
  cuuint64_t gd[5] = {cols, 2, 4, 4, rows / 32};
  cuuint64_t gs[4] = {rs, (perm ? 8 : 2) * rs, (perm ? 2 : 8) * rs, 32 * rs};
  cuuint32_t bd[5] = {64, 2, 4, 4, 2}, es[5] = {1, 1, 1, 1, 1};
  enc(m, CU_TENSOR_MAP_DATA_TYPE_BFLOAT16, 5, (void*)ptr, gd, gs, bd, es, CU_TENSOR_MAP_INTERLEAVE_NONE, CU_TENSOR_MAP_SWIZZLE_128B,
      CU_TENSOR_MAP_L2_PROMOTION_L2_256B, CU_TENSOR_MAP_FLOAT_OOB_FILL_NONE);
}

void make_2d(EncodeTiledFn enc, CUtensorMap* m, const void* ptr, uint64_t rows, uint64_t cols, uint32_t box_rows) {
  cuuint64_t gd[2] = {cols, rows}, gs[1] = {cols * 2}; cuuint32_t bd[2] = {64, box_rows}, es[2] = {1, 1};
  enc(m, CU_TENSOR_MAP_DATA_TYPE_BFLOAT16, 2, (void*)ptr, gd, gs, bd, es, CU_TENSOR_MAP_INTERLEAVE_NONE, CU_TENSOR_MAP_SWIZZLE_128B,
      CU_TENSOR_MAP_L2_PROMOTION_L2_256B, CU_TENSOR_MAP_FLOAT_OOB_FILL_NONE);
}

}

extern "C" void kernel_launch(void* const* d_in, const int* in_sizes, int n_in, void* d_out, int out_size) {
  const __nv_bfloat16* x = (const __nv_bfloat16*)d_in[0];
  const __nv_bfloat16* wqkv = (const __nv_bfloat16*)d_in[1];
  const __nv_bfloat16* wo = (const __nv_bfloat16*)d_in[2];
  const __nv_bfloat16* wg = (const __nv_bfloat16*)d_in[4];
  const __nv_bfloat16* wu = (const __nv_bfloat16*)d_in[5];
  const __nv_bfloat16* wd = (const __nv_bfloat16*)d_in[6];

  void* fn = nullptr; cudaDriverEntryPointQueryResult qr;
  cudaGetDriverEntryPoint("cuTensorMapEncodeTiled", &fn, cudaEnableDefault, &qr);
  EncodeTiledFn enc = (EncodeTiledFn)fn;
  Params prm;
  make_2d(enc, &prm.x, x, S_, D_, 128);
  make_wmap(enc, &prm.wqkv_n, wqkv, D_, 3 * D_, false);
  make_wmap(enc, &prm.wqkv_p, wqkv, D_, 3 * D_, true);
  make_wmap(enc, &prm.wo_p, wo, D_, D_, true);
  make_wmap(enc, &prm.wg_p, wg, D_, F_, true);
  make_wmap(enc, &prm.wu_p, wu, D_, F_, true);
  make_wmap(enc, &prm.wd_p, wd, F_, D_, true);
  prm.xin = x; prm.out = (__nv_bfloat16*)d_out;
  cudaGetSymbolAddress((void**)&prm.sc, g_scratch);
  prm.sc = (Scratch*)(((uintptr_t)prm.sc + (2u << 20) - 1) & ~(uintptr_t)((2u << 20) - 1));
  cudaFuncSetAttribute(fused_kernel, cudaFuncAttributeMaxDynamicSharedMemorySize, SMEM_BYTES);
  cudaLaunchConfig_t cfg = {};
  cfg.gridDim = dim3(132); cfg.blockDim = dim3(384); cfg.dynamicSmemBytes = SMEM_BYTES; cfg.stream = cudaStreamPerThread;
  cudaLaunchAttribute at[1];
  at[0].id = cudaLaunchAttributeClusterDimension; at[0].val.clusterDim.x = 2; at[0].val.clusterDim.y = 1; at[0].val.clusterDim.z = 1;
  cfg.attrs = at; cfg.numAttrs = 1;
  int ncl = 0;
  cudaOccupancyMaxActiveClusters(&ncl, fused_kernel, &cfg);
  const bool last = HLAST && ncl >= 66;
  for (int ci = 0; ci < 66; ci++) {
    const int tq = ci - 4;
    const int mp = (ci < 4 || ci >= 64) ? 0 : (tq < 32 ? tq & 7 : 1 + (tq - 32) % 7);
    const int j = ci < 4 ? (last ? 4 : 2) + ci : ci >= 64 ? ci - 58 : (tq < 32 ? tq >> 3 : 4 + (tq - 32) / 7);
    prm.role[ci] = (last ? ci >= 64 : ci < 2) ? 64 : mp | (j << 3);
  }
  cudaLaunchKernelEx(&cfg, fused_kernel, prm);
}
```

```cpp
#include <cuda_runtime.h>
#include <cuda_bf16.h>
#include <cuda.h>
#include <stdint.h>

#pragma nv_diag_suppress 177

namespace {

constexpr int S_ = 2048, D_ = 1024, F_ = 3584;
constexpr int NSLOT = 12;
constexpr uint32_t SLOT = 16384;
constexpr uint32_t OFF_STG = NSLOT * SLOT;
constexpr uint32_t OFF_LN = OFF_STG + 32768;
constexpr uint32_t OFF_ONES = OFF_LN + 2048;
constexpr uint32_t OFF_BAR = OFF_ONES + 256;
constexpr uint32_t SMEM_BYTES = OFF_BAR + 512;
constexpr uint32_t OFF_CSKV = OFF_STG + 28672, OFF_CSQ = OFF_STG + 20480, OFF_CSGU = OFF_STG;

struct RowBlock {
  uint8_t act[3][16 * SLOT];
  uint8_t h[56 * SLOT];
  float2 stats[4][128][8];
  uint32_t flag[2][4][32];
  uint8_t pad[(2u << 20) - 104 * SLOT - 32768 - 1024];
};
struct Scratch {
  RowBlock rb[16];
  float cs[2][3072 + 2 * F_];
  float kv[2][2][8][4224];
  uint32_t kvcnt[2][8][32];
  uint32_t cscnt[12][32];
  uint32_t epoch;
};
__device__ __align__(1024) uint8_t g_scratch[sizeof(Scratch) + (2u << 20)];

struct Params {
  CUtensorMap x, wqkv_n, wqkv_p, wo_p, wg_p, wu_p, wd_p;
  __nv_bfloat16* out;
  Scratch* sc;
  int role[66];
};

__device__ __forceinline__ uint32_t smem_u32(const void* p) { return (uint32_t)__cvta_generic_to_shared(p); }
__device__ __forceinline__ void mbar_init(uint32_t bar, uint32_t count) { asm volatile("mbarrier.init.shared::cta.b64 [%0], %1;" :: "r"(bar), "r"(count) : "memory"); }
__device__ __forceinline__ void mbar_expect_tx(uint32_t bar, uint32_t bytes) { asm volatile("mbarrier.arrive.expect_tx.shared::cta.b64 _, [%0], %1;" :: "r"(bar), "r"(bytes) : "memory"); }
__device__ __forceinline__ void mbar_arrive(uint32_t bar) { asm volatile("mbarrier.arrive.shared::cta.b64 _, [%0];" :: "r"(bar) : "memory"); }
__device__ __forceinline__ void mbar_arrive_if(uint32_t bar, bool pred) {
  asm volatile("{\n.reg .pred p;\nsetp.ne.b32 p, %1, 0;\n@p mbarrier.arrive.shared::cta.b64 _, [%0];\n}\n" :: "r"(bar), "r"((uint32_t)pred) : "memory");
}
__device__ __forceinline__ void mbar_arrive_remote_if(uint32_t cluster_addr, bool pred) {
  asm volatile("{\n.reg .pred p;\nsetp.ne.b32 p, %1, 0;\n@p mbarrier.arrive.shared::cluster.b64 _, [%0];\n}\n" :: "r"(cluster_addr), "r"((uint32_t)pred) : "memory");
}
__device__ __forceinline__ uint32_t mapa(uint32_t addr, uint32_t cta) { uint32_t r; asm("mapa.shared::cluster.u32 %0, %1, %2;" : "=r"(r) : "r"(addr), "r"(cta)); return r; }
__device__ __forceinline__ void st_f2_if(float2* ptr, float a, float b, bool pred) {
  asm volatile("{\n.reg .pred p;\nsetp.ne.b32 p, %3, 0;\n@p st.global.v2.f32 [%0], {%1, %2};\n}\n" :: "l"(ptr), "f"(a), "f"(b), "r"((uint32_t)pred) : "memory");
}
__device__ __forceinline__ void red_add_f32_if(float* ptr, float v, bool pred) {
  asm volatile("{\n.reg .pred p;\nsetp.ne.b32 p, %2, 0;\n@p red.relaxed.gpu.global.add.f32 [%0], %1;\n}\n" :: "l"(ptr), "f"(v), "r"((uint32_t)pred) : "memory");
}
__device__ __forceinline__ void mbar_wait(uint32_t bar, uint32_t parity) {
  asm volatile("{\n.reg .pred p;\n.reg .b32 n;\nmov.b32 n, 0;\nWAIT_LOOP:\n"
               "mbarrier.try_wait.parity.shared::cta.b64 p, [%0], %1;\n@p bra WAIT_DONE;\n"
               "add.u32 n, n, 1;\nsetp.lt.u32 p, n, 1048576;\n@p bra WAIT_LOOP;\ntrap;\nWAIT_DONE:\n}\n" :: "r"(bar), "r"(parity) : "memory");
}
__device__ __forceinline__ uint32_t ld_acquire(const uint32_t* p) { uint32_t v; asm volatile("ld.acquire.gpu.global.u32 %0, [%1];" : "=r"(v) : "l"(p) : "memory"); return v; }
__device__ __forceinline__ void poll_eq(const uint32_t* p, uint32_t want) {
  uint32_t n = 0;
  while (ld_acquire(p) != want) { if (++n > (1u << 20)) __trap(); }
}
__device__ __forceinline__ void tma_2d(uint32_t dst, const CUtensorMap* m, uint32_t bar, int c0, int c1) {
  asm volatile("cp.async.bulk.tensor.2d.shared::cluster.global.mbarrier::complete_tx::bytes [%0], [%1, {%3, %4}], [%2];"
    :: "r"(dst), "l"((uint64_t)m), "r"(bar), "r"(c0), "r"(c1) : "memory");
}
__device__ __forceinline__ void tma_5d_mc(uint32_t dst, const CUtensorMap* m, uint32_t bar, int c0, int c4) {
  asm volatile("cp.async.bulk.tensor.5d.shared::cluster.global.mbarrier::complete_tx::bytes.multicast::cluster [%0], [%1, {%3, %5, %5, %5, %4}], [%2], %6;"
    :: "r"(dst), "l"((uint64_t)m), "r"(bar), "r"(c0), "r"(c4), "r"(0), "h"((uint16_t)3) : "memory");
}
__device__ __forceinline__ void tma_5d(uint32_t dst, const CUtensorMap* m, uint32_t bar, int c0, int c4) {
  asm volatile("cp.async.bulk.tensor.5d.shared::cluster.global.mbarrier::complete_tx::bytes [%0], [%1, {%3, %5, %5, %5, %4}], [%2];"
    :: "r"(dst), "l"((uint64_t)m), "r"(bar), "r"(c0), "r"(c4), "r"(0) : "memory");
}
__device__ __forceinline__ void tma_5d_prefetch(const CUtensorMap* m, int c0, int c4) {
  asm volatile("cp.async.bulk.prefetch.tensor.5d.L2.global.tile [%0, {%1, %3, %3, %3, %2}];" :: "l"((uint64_t)m), "r"(c0), "r"(c4), "r"(0) : "memory");
}
__device__ __forceinline__ void bulk_load(uint32_t dst, const void* src, uint32_t bytes, uint32_t bar) {
  asm volatile("cp.async.bulk.shared::cluster.global.mbarrier::complete_tx::bytes [%0], [%1], %2, [%3];"
    :: "r"(dst), "l"((uint64_t)src), "r"(bytes), "r"(bar) : "memory");
}
__device__ __forceinline__ void bulk_reduce_f32(void* dst, uint32_t src, uint32_t bytes) {
  asm volatile("cp.reduce.async.bulk.global.shared::cta.bulk_group.add.f32 [%0], [%1], %2;" :: "l"((uint64_t)dst), "r"(src), "r"(bytes) : "memory");
}
__device__ __forceinline__ void wgmma_fence() { asm volatile("wgmma.fence.sync.aligned;" ::: "memory"); }
__device__ __forceinline__ void wgmma_commit() { asm volatile("wgmma.commit_group.sync.aligned;" ::: "memory"); }
template<int N> __device__ __forceinline__ void wgmma_wait() { asm volatile("wgmma.wait_group.sync.aligned %0;" :: "n"(N) : "memory"); }
__device__ __forceinline__ void cluster_wait() { asm volatile("barrier.cluster.wait.acquire.aligned;" ::: "memory"); }
__device__ __forceinline__ void fence_async_smem() { asm volatile("fence.proxy.async.shared::cta;" ::: "memory"); }
__device__ __forceinline__ void fence_async_global() { asm volatile("fence.proxy.async.global;" ::: "memory"); }
__device__ __forceinline__ void fence_gpu() { asm volatile("fence.acq_rel.gpu;" ::: "memory"); }
__device__ __forceinline__ void wg_bar(int id) { asm volatile("bar.sync %0, 128;" :: "r"(id) : "memory"); }
__device__ __forceinline__ void st_relaxed(uint32_t* p, uint32_t v) { asm volatile("st.relaxed.gpu.global.u32 [%0], %1;" :: "l"(p), "r"(v) : "memory"); }
__device__ __forceinline__ void red_add_u32(uint32_t* p, uint32_t v) { asm volatile("red.relaxed.gpu.global.add.u32 [%0], %1;" :: "l"(p), "r"(v) : "memory"); }
__device__ __forceinline__ void red_add_v4(float* p, float a, float b, float c, float d) {
  asm volatile("red.relaxed.gpu.global.add.v4.f32 [%0], {%1, %2, %3, %4};" :: "l"(p), "f"(a), "f"(b), "f"(c), "f"(d) : "memory");
}
__device__ __forceinline__ void stmatrix_x4(uint32_t addr, uint32_t r0, uint32_t r1, uint32_t r2, uint32_t r3) {
  asm volatile("stmatrix.sync.aligned.m8n8.x4.shared.b16 [%0], {%1, %2, %3, %4};" :: "r"(addr), "r"(r0), "r"(r1), "r"(r2), "r"(r3) : "memory");
}
__device__ __forceinline__ uint32_t lds_u32(uint32_t addr) { uint32_t v; asm volatile("ld.shared.u32 %0, [%1];" : "=r"(v) : "r"(addr) : "memory"); return v; }
__device__ __forceinline__ void sts_u32(uint32_t addr, uint32_t v) { asm volatile("st.shared.u32 [%0], %1;" :: "r"(addr), "r"(v) : "memory"); }
__device__ __forceinline__ void sts_v4(uint32_t addr, uint4 v) { asm volatile("st.shared.v4.u32 [%0], {%1, %2, %3, %4};" :: "r"(addr), "r"(v.x), "r"(v.y), "r"(v.z), "r"(v.w) : "memory"); }
__device__ __forceinline__ uint32_t pack_bf16(float lo, float hi) { uint32_t r; asm("cvt.rn.bf16x2.f32 %0, %1, %2;" : "=r"(r) : "f"(hi), "f"(lo)); return r; }
__device__ __forceinline__ float bf_lo(uint32_t v) { return __uint_as_float(v << 16); }
__device__ __forceinline__ float bf_hi(uint32_t v) { return __uint_as_float(v & 0xffff0000u); }
__device__ __forceinline__ float ex2f(float x) { float r; asm("ex2.approx.ftz.f32 %0, %1;" : "=f"(r) : "f"(x)); return r; }
__device__ __forceinline__ float rcpf(float x) { float r; asm("rcp.approx.ftz.f32 %0, %1;" : "=f"(r) : "f"(x)); return r; }
__device__ __forceinline__ uint32_t make_desc(uint32_t addr, uint32_t lbo) { return ((addr & 0x3FFFF) >> 4) | ((lbo >> 4) << 16); }
__device__ __forceinline__ bool mbar_test(uint32_t bar, uint32_t parity) {
  uint32_t ok;
  asm volatile("{\n.reg .pred p;\nmbarrier.test_wait.parity.shared::cta.b64 p, [%1], %2;\nselp.u32 %0, 1, 0, p;\n}\n" : "=r"(ok) : "r"(bar), "r"(parity) : "memory");
  return ok;
}
__device__ __forceinline__ int lane_id() { int r; asm volatile("mov.u32 %0, %%laneid;" : "=r"(r)); return r; }
#define load_epoch() (__ldcg(&prm.sc->epoch) + 1)
__device__ __forceinline__ bool elect_one() {
  uint32_t r;
  asm volatile("{\n.reg .pred p;\nelect.sync _|p, 0xffffffff;\nselp.u32 %0, 1, 0, p;\n}\n" : "=r"(r));
  return r;
}
__device__ __forceinline__ uint32_t hadd2(uint32_t a, uint32_t b) { uint32_t r; asm("add.rn.bf16x2 %0, %1, %2;" : "=r"(r) : "r"(a), "r"(b)); return r; }
__device__ __forceinline__ uint32_t hmul2(uint32_t a, uint32_t b) { uint32_t r; asm("mul.rn.bf16x2 %0, %1, %2;" : "=r"(r) : "r"(a), "r"(b)); return r; }

template<bool INIT> __device__ __forceinline__ void wgmma_n256_ss(float* d, uint32_t da, uint32_t db) {
  if constexpr (INIT) {
  asm volatile("{\n.reg .pred p;\n.reg .b64 da, db;\nsetp.ne.b32 p, 0, 0;\nmov.b64 da, {%128, 0x40000040};\nmov.b64 db, {%129, 0x40000040};\nwgmma.mma_async.sync.aligned.m64n256k16.f32.bf16.bf16 {%0, %1, %2, %3, %4, %5, %6, %7, %8, %9, %10, %11, %12, %13, %14, %15, %16, %17, %18, %19, %20, %21, %22, %23, %24, %25, %26, %27, %28, %29, %30, %31, %32, %33, %34, %35, %36, %37, %38, %39, %40, %41, %42, %43, %44, %45, %46, %47, %48, %49, %50, %51, %52, %53, %54, %55, %56, %57, %58, %59, %60, %61, %62, %63, %64, %65, %66, %67, %68, %69, %70, %71, %72, %73, %74, %75, %76, %77, %78, %79, %80, %81, %82, %83, %84, %85, %86, %87, %88, %89, %90, %91, %92, %93, %94, %95, %96, %97, %98, %99, %100, %101, %102, %103, %104, %105, %106, %107, %108, %109, %110, %111, %112, %113, %114, %115, %116, %117, %118, %119, %120, %121, %122, %123, %124, %125, %126, %127}, da, db, p, 1, 1, 0, 1;\n}\n"
    : "=f"(d[0]), "=f"(d[1]), "=f"(d[2]), "=f"(d[3]), "=f"(d[4]), "=f"(d[5]), "=f"(d[6]), "=f"(d[7]), "=f"(d[8]), "=f"(d[9]), "=f"(d[10]), "=f"(d[11]), "=f"(d[12]), "=f"(d[13]), "=f"(d[14]), "=f"(d[15]), "=f"(d[16]), "=f"(d[17]), "=f"(d[18]), "=f"(d[19]), "=f"(d[20]), "=f"(d[21]), "=f"(d[22]), "=f"(d[23]), "=f"(d[24]), "=f"(d[25]), "=f"(d[26]), "=f"(d[27]), "=f"(d[28]), "=f"(d[29]), "=f"(d[30]), "=f"(d[31]), "=f"(d[32]), "=f"(d[33]), "=f"(d[34]), "=f"(d[35]), "=f"(d[36]), "=f"(d[37]), "=f"(d[38]), "=f"(d[39]), "=f"(d[40]), "=f"(d[41]), "=f"(d[42]), "=f"(d[43]), "=f"(d[44]), "=f"(d[45]), "=f"(d[46]), "=f"(d[47]), "=f"(d[48]), "=f"(d[49]), "=f"(d[50]), "=f"(d[51]), "=f"(d[52]), "=f"(d[53]), "=f"(d[54]), "=f"(d[55]), "=f"(d[56]), "=f"(d[57]), "=f"(d[58]), "=f"(d[59]), "=f"(d[60]), "=f"(d[61]), "=f"(d[62]), "=f"(d[63]), "=f"(d[64]), "=f"(d[65]), "=f"(d[66]), "=f"(d[67]), "=f"(d[68]), "=f"(d[69]), "=f"(d[70]), "=f"(d[71]), "=f"(d[72]), "=f"(d[73]), "=f"(d[74]), "=f"(d[75]), "=f"(d[76]), "=f"(d[77]), "=f"(d[78]), "=f"(d[79]), "=f"(d[80]), "=f"(d[81]), "=f"(d[82]), "=f"(d[83]), "=f"(d[84]), "=f"(d[85]), "=f"(d[86]), "=f"(d[87]), "=f"(d[88]), "=f"(d[89]), "=f"(d[90]), "=f"(d[91]), "=f"(d[92]), "=f"(d[93]), "=f"(d[94]), "=f"(d[95]), "=f"(d[96]), "=f"(d[97]), "=f"(d[98]), "=f"(d[99]), "=f"(d[100]), "=f"(d[101]), "=f"(d[102]), "=f"(d[103]), "=f"(d[104]), "=f"(d[105]), "=f"(d[106]), "=f"(d[107]), "=f"(d[108]), "=f"(d[109]), "=f"(d[110]), "=f"(d[111]), "=f"(d[112]), "=f"(d[113]), "=f"(d[114]), "=f"(d[115]), "=f"(d[116]), "=f"(d[117]), "=f"(d[118]), "=f"(d[119]), "=f"(d[120]), "=f"(d[121]), "=f"(d[122]), "=f"(d[123]), "=f"(d[124]), "=f"(d[125]), "=f"(d[126]), "=f"(d[127])
    : "r"(da), "r"(db));
  } else {
  asm volatile("{\n.reg .pred p;\n.reg .b64 da, db;\nsetp.ne.b32 p, 1, 0;\nmov.b64 da, {%128, 0x40000040};\nmov.b64 db, {%129, 0x40000040};\nwgmma.mma_async.sync.aligned.m64n256k16.f32.bf16.bf16 {%0, %1, %2, %3, %4, %5, %6, %7, %8, %9, %10, %11, %12, %13, %14, %15, %16, %17, %18, %19, %20, %21, %22, %23, %24, %25, %26, %27, %28, %29, %30, %31, %32, %33, %34, %35, %36, %37, %38, %39, %40, %41, %42, %43, %44, %45, %46, %47, %48, %49, %50, %51, %52, %53, %54, %55, %56, %57, %58, %59, %60, %61, %62, %63, %64, %65, %66, %67, %68, %69, %70, %71, %72, %73, %74, %75, %76, %77, %78, %79, %80, %81, %82, %83, %84, %85, %86, %87, %88, %89, %90, %91, %92, %93, %94, %95, %96, %97, %98, %99, %100, %101, %102, %103, %104, %105, %106, %107, %108, %109, %110, %111, %112, %113, %114, %115, %116, %117, %118, %119, %120, %121, %122, %123, %124, %125, %126, %127}, da, db, p, 1, 1, 0, 1;\n}\n"
    : "+f"(d[0]), "+f"(d[1]), "+f"(d[2]), "+f"(d[3]), "+f"(d[4]), "+f"(d[5]), "+f"(d[6]), "+f"(d[7]), "+f"(d[8]), "+f"(d[9]), "+f"(d[10]), "+f"(d[11]), "+f"(d[12]), "+f"(d[13]), "+f"(d[14]), "+f"(d[15]), "+f"(d[16]), "+f"(d[17]), "+f"(d[18]), "+f"(d[19]), "+f"(d[20]), "+f"(d[21]), "+f"(d[22]), "+f"(d[23]), "+f"(d[24]), "+f"(d[25]), "+f"(d[26]), "+f"(d[27]), "+f"(d[28]), "+f"(d[29]), "+f"(d[30]), "+f"(d[31]), "+f"(d[32]), "+f"(d[33]), "+f"(d[34]), "+f"(d[35]), "+f"(d[36]), "+f"(d[37]), "+f"(d[38]), "+f"(d[39]), "+f"(d[40]), "+f"(d[41]), "+f"(d[42]), "+f"(d[43]), "+f"(d[44]), "+f"(d[45]), "+f"(d[46]), "+f"(d[47]), "+f"(d[48]), "+f"(d[49]), "+f"(d[50]), "+f"(d[51]), "+f"(d[52]), "+f"(d[53]), "+f"(d[54]), "+f"(d[55]), "+f"(d[56]), "+f"(d[57]), "+f"(d[58]), "+f"(d[59]), "+f"(d[60]), "+f"(d[61]), "+f"(d[62]), "+f"(d[63]), "+f"(d[64]), "+f"(d[65]), "+f"(d[66]), "+f"(d[67]), "+f"(d[68]), "+f"(d[69]), "+f"(d[70]), "+f"(d[71]), "+f"(d[72]), "+f"(d[73]), "+f"(d[74]), "+f"(d[75]), "+f"(d[76]), "+f"(d[77]), "+f"(d[78]), "+f"(d[79]), "+f"(d[80]), "+f"(d[81]), "+f"(d[82]), "+f"(d[83]), "+f"(d[84]), "+f"(d[85]), "+f"(d[86]), "+f"(d[87]), "+f"(d[88]), "+f"(d[89]), "+f"(d[90]), "+f"(d[91]), "+f"(d[92]), "+f"(d[93]), "+f"(d[94]), "+f"(d[95]), "+f"(d[96]), "+f"(d[97]), "+f"(d[98]), "+f"(d[99]), "+f"(d[100]), "+f"(d[101]), "+f"(d[102]), "+f"(d[103]), "+f"(d[104]), "+f"(d[105]), "+f"(d[106]), "+f"(d[107]), "+f"(d[108]), "+f"(d[109]), "+f"(d[110]), "+f"(d[111]), "+f"(d[112]), "+f"(d[113]), "+f"(d[114]), "+f"(d[115]), "+f"(d[116]), "+f"(d[117]), "+f"(d[118]), "+f"(d[119]), "+f"(d[120]), "+f"(d[121]), "+f"(d[122]), "+f"(d[123]), "+f"(d[124]), "+f"(d[125]), "+f"(d[126]), "+f"(d[127])
    : "r"(da), "r"(db));
  }
}
template<bool INIT> __device__ __forceinline__ void wgmma_n128_ss(float* d, uint32_t da, uint32_t db) {
  if constexpr (INIT) {
  asm volatile("{\n.reg .pred p;\n.reg .b64 da, db;\nsetp.ne.b32 p, 0, 0;\nmov.b64 da, {%64, 0x40000040};\nmov.b64 db, {%65, 0x40000040};\nwgmma.mma_async.sync.aligned.m64n128k16.f32.bf16.bf16 {%0, %1, %2, %3, %4, %5, %6, %7, %8, %9, %10, %11, %12, %13, %14, %15, %16, %17, %18, %19, %20, %21, %22, %23, %24, %25, %26, %27, %28, %29, %30, %31, %32, %33, %34, %35, %36, %37, %38, %39, %40, %41, %42, %43, %44, %45, %46, %47, %48, %49, %50, %51, %52, %53, %54, %55, %56, %57, %58, %59, %60, %61, %62, %63}, da, db, p, 1, 1, 0, 1;\n}\n"
    : "=f"(d[0]), "=f"(d[1]), "=f"(d[2]), "=f"(d[3]), "=f"(d[4]), "=f"(d[5]), "=f"(d[6]), "=f"(d[7]), "=f"(d[8]), "=f"(d[9]), "=f"(d[10]), "=f"(d[11]), "=f"(d[12]), "=f"(d[13]), "=f"(d[14]), "=f"(d[15]), "=f"(d[16]), "=f"(d[17]), "=f"(d[18]), "=f"(d[19]), "=f"(d[20]), "=f"(d[21]), "=f"(d[22]), "=f"(d[23]), "=f"(d[24]), "=f"(d[25]), "=f"(d[26]), "=f"(d[27]), "=f"(d[28]), "=f"(d[29]), "=f"(d[30]), "=f"(d[31]), "=f"(d[32]), "=f"(d[33]), "=f"(d[34]), "=f"(d[35]), "=f"(d[36]), "=f"(d[37]), "=f"(d[38]), "=f"(d[39]), "=f"(d[40]), "=f"(d[41]), "=f"(d[42]), "=f"(d[43]), "=f"(d[44]), "=f"(d[45]), "=f"(d[46]), "=f"(d[47]), "=f"(d[48]), "=f"(d[49]), "=f"(d[50]), "=f"(d[51]), "=f"(d[52]), "=f"(d[53]), "=f"(d[54]), "=f"(d[55]), "=f"(d[56]), "=f"(d[57]), "=f"(d[58]), "=f"(d[59]), "=f"(d[60]), "=f"(d[61]), "=f"(d[62]), "=f"(d[63])
    : "r"(da), "r"(db));
  } else {
  asm volatile("{\n.reg .pred p;\n.reg .b64 da, db;\nsetp.ne.b32 p, 1, 0;\nmov.b64 da, {%64, 0x40000040};\nmov.b64 db, {%65, 0x40000040};\nwgmma.mma_async.sync.aligned.m64n128k16.f32.bf16.bf16 {%0, %1, %2, %3, %4, %5, %6, %7, %8, %9, %10, %11, %12, %13, %14, %15, %16, %17, %18, %19, %20, %21, %22, %23, %24, %25, %26, %27, %28, %29, %30, %31, %32, %33, %34, %35, %36, %37, %38, %39, %40, %41, %42, %43, %44, %45, %46, %47, %48, %49, %50, %51, %52, %53, %54, %55, %56, %57, %58, %59, %60, %61, %62, %63}, da, db, p, 1, 1, 0, 1;\n}\n"
    : "+f"(d[0]), "+f"(d[1]), "+f"(d[2]), "+f"(d[3]), "+f"(d[4]), "+f"(d[5]), "+f"(d[6]), "+f"(d[7]), "+f"(d[8]), "+f"(d[9]), "+f"(d[10]), "+f"(d[11]), "+f"(d[12]), "+f"(d[13]), "+f"(d[14]), "+f"(d[15]), "+f"(d[16]), "+f"(d[17]), "+f"(d[18]), "+f"(d[19]), "+f"(d[20]), "+f"(d[21]), "+f"(d[22]), "+f"(d[23]), "+f"(d[24]), "+f"(d[25]), "+f"(d[26]), "+f"(d[27]), "+f"(d[28]), "+f"(d[29]), "+f"(d[30]), "+f"(d[31]), "+f"(d[32]), "+f"(d[33]), "+f"(d[34]), "+f"(d[35]), "+f"(d[36]), "+f"(d[37]), "+f"(d[38]), "+f"(d[39]), "+f"(d[40]), "+f"(d[41]), "+f"(d[42]), "+f"(d[43]), "+f"(d[44]), "+f"(d[45]), "+f"(d[46]), "+f"(d[47]), "+f"(d[48]), "+f"(d[49]), "+f"(d[50]), "+f"(d[51]), "+f"(d[52]), "+f"(d[53]), "+f"(d[54]), "+f"(d[55]), "+f"(d[56]), "+f"(d[57]), "+f"(d[58]), "+f"(d[59]), "+f"(d[60]), "+f"(d[61]), "+f"(d[62]), "+f"(d[63])
    : "r"(da), "r"(db));
  }
}
template<bool INIT> __device__ __forceinline__ void wgmma_n256_nn(float* d, uint32_t da, uint32_t db) {
  if constexpr (INIT) {
  asm volatile("{\n.reg .pred p;\n.reg .b64 da, db;\nsetp.ne.b32 p, 0, 0;\nmov.b64 da, {%128, 8};\nmov.b64 db, {%129, 8};\nwgmma.mma_async.sync.aligned.m64n256k16.f32.bf16.bf16 {%0, %1, %2, %3, %4, %5, %6, %7, %8, %9, %10, %11, %12, %13, %14, %15, %16, %17, %18, %19, %20, %21, %22, %23, %24, %25, %26, %27, %28, %29, %30, %31, %32, %33, %34, %35, %36, %37, %38, %39, %40, %41, %42, %43, %44, %45, %46, %47, %48, %49, %50, %51, %52, %53, %54, %55, %56, %57, %58, %59, %60, %61, %62, %63, %64, %65, %66, %67, %68, %69, %70, %71, %72, %73, %74, %75, %76, %77, %78, %79, %80, %81, %82, %83, %84, %85, %86, %87, %88, %89, %90, %91, %92, %93, %94, %95, %96, %97, %98, %99, %100, %101, %102, %103, %104, %105, %106, %107, %108, %109, %110, %111, %112, %113, %114, %115, %116, %117, %118, %119, %120, %121, %122, %123, %124, %125, %126, %127}, da, db, p, 1, 1, 0, 0;\n}\n"
    : "=f"(d[0]), "=f"(d[1]), "=f"(d[2]), "=f"(d[3]), "=f"(d[4]), "=f"(d[5]), "=f"(d[6]), "=f"(d[7]), "=f"(d[8]), "=f"(d[9]), "=f"(d[10]), "=f"(d[11]), "=f"(d[12]), "=f"(d[13]), "=f"(d[14]), "=f"(d[15]), "=f"(d[16]), "=f"(d[17]), "=f"(d[18]), "=f"(d[19]), "=f"(d[20]), "=f"(d[21]), "=f"(d[22]), "=f"(d[23]), "=f"(d[24]), "=f"(d[25]), "=f"(d[26]), "=f"(d[27]), "=f"(d[28]), "=f"(d[29]), "=f"(d[30]), "=f"(d[31]), "=f"(d[32]), "=f"(d[33]), "=f"(d[34]), "=f"(d[35]), "=f"(d[36]), "=f"(d[37]), "=f"(d[38]), "=f"(d[39]), "=f"(d[40]), "=f"(d[41]), "=f"(d[42]), "=f"(d[43]), "=f"(d[44]), "=f"(d[45]), "=f"(d[46]), "=f"(d[47]), "=f"(d[48]), "=f"(d[49]), "=f"(d[50]), "=f"(d[51]), "=f"(d[52]), "=f"(d[53]), "=f"(d[54]), "=f"(d[55]), "=f"(d[56]), "=f"(d[57]), "=f"(d[58]), "=f"(d[59]), "=f"(d[60]), "=f"(d[61]), "=f"(d[62]), "=f"(d[63]), "=f"(d[64]), "=f"(d[65]), "=f"(d[66]), "=f"(d[67]), "=f"(d[68]), "=f"(d[69]), "=f"(d[70]), "=f"(d[71]), "=f"(d[72]), "=f"(d[73]), "=f"(d[74]), "=f"(d[75]), "=f"(d[76]), "=f"(d[77]), "=f"(d[78]), "=f"(d[79]), "=f"(d[80]), "=f"(d[81]), "=f"(d[82]), "=f"(d[83]), "=f"(d[84]), "=f"(d[85]), "=f"(d[86]), "=f"(d[87]), "=f"(d[88]), "=f"(d[89]), "=f"(d[90]), "=f"(d[91]), "=f"(d[92]), "=f"(d[93]), "=f"(d[94]), "=f"(d[95]), "=f"(d[96]), "=f"(d[97]), "=f"(d[98]), "=f"(d[99]), "=f"(d[100]), "=f"(d[101]), "=f"(d[102]), "=f"(d[103]), "=f"(d[104]), "=f"(d[105]), "=f"(d[106]), "=f"(d[107]), "=f"(d[108]), "=f"(d[109]), "=f"(d[110]), "=f"(d[111]), "=f"(d[112]), "=f"(d[113]), "=f"(d[114]), "=f"(d[115]), "=f"(d[116]), "=f"(d[117]), "=f"(d[118]), "=f"(d[119]), "=f"(d[120]), "=f"(d[121]), "=f"(d[122]), "=f"(d[123]), "=f"(d[124]), "=f"(d[125]), "=f"(d[126]), "=f"(d[127])
    : "r"(da), "r"(db));
  } else {
  asm volatile("{\n.reg .pred p;\n.reg .b64 da, db;\nsetp.ne.b32 p, 1, 0;\nmov.b64 da, {%128, 8};\nmov.b64 db, {%129, 8};\nwgmma.mma_async.sync.aligned.m64n256k16.f32.bf16.bf16 {%0, %1, %2, %3, %4, %5, %6, %7, %8, %9, %10, %11, %12, %13, %14, %15, %16, %17, %18, %19, %20, %21, %22, %23, %24, %25, %26, %27, %28, %29, %30, %31, %32, %33, %34, %35, %36, %37, %38, %39, %40, %41, %42, %43, %44, %45, %46, %47, %48, %49, %50, %51, %52, %53, %54, %55, %56, %57, %58, %59, %60, %61, %62, %63, %64, %65, %66, %67, %68, %69, %70, %71, %72, %73, %74, %75, %76, %77, %78, %79, %80, %81, %82, %83, %84, %85, %86, %87, %88, %89, %90, %91, %92, %93, %94, %95, %96, %97, %98, %99, %100, %101, %102, %103, %104, %105, %106, %107, %108, %109, %110, %111, %112, %113, %114, %115, %116, %117, %118, %119, %120, %121, %122, %123, %124, %125, %126, %127}, da, db, p, 1, 1, 0, 0;\n}\n"
    : "+f"(d[0]), "+f"(d[1]), "+f"(d[2]), "+f"(d[3]), "+f"(d[4]), "+f"(d[5]), "+f"(d[6]), "+f"(d[7]), "+f"(d[8]), "+f"(d[9]), "+f"(d[10]), "+f"(d[11]), "+f"(d[12]), "+f"(d[13]), "+f"(d[14]), "+f"(d[15]), "+f"(d[16]), "+f"(d[17]), "+f"(d[18]), "+f"(d[19]), "+f"(d[20]), "+f"(d[21]), "+f"(d[22]), "+f"(d[23]), "+f"(d[24]), "+f"(d[25]), "+f"(d[26]), "+f"(d[27]), "+f"(d[28]), "+f"(d[29]), "+f"(d[30]), "+f"(d[31]), "+f"(d[32]), "+f"(d[33]), "+f"(d[34]), "+f"(d[35]), "+f"(d[36]), "+f"(d[37]), "+f"(d[38]), "+f"(d[39]), "+f"(d[40]), "+f"(d[41]), "+f"(d[42]), "+f"(d[43]), "+f"(d[44]), "+f"(d[45]), "+f"(d[46]), "+f"(d[47]), "+f"(d[48]), "+f"(d[49]), "+f"(d[50]), "+f"(d[51]), "+f"(d[52]), "+f"(d[53]), "+f"(d[54]), "+f"(d[55]), "+f"(d[56]), "+f"(d[57]), "+f"(d[58]), "+f"(d[59]), "+f"(d[60]), "+f"(d[61]), "+f"(d[62]), "+f"(d[63]), "+f"(d[64]), "+f"(d[65]), "+f"(d[66]), "+f"(d[67]), "+f"(d[68]), "+f"(d[69]), "+f"(d[70]), "+f"(d[71]), "+f"(d[72]), "+f"(d[73]), "+f"(d[74]), "+f"(d[75]), "+f"(d[76]), "+f"(d[77]), "+f"(d[78]), "+f"(d[79]), "+f"(d[80]), "+f"(d[81]), "+f"(d[82]), "+f"(d[83]), "+f"(d[84]), "+f"(d[85]), "+f"(d[86]), "+f"(d[87]), "+f"(d[88]), "+f"(d[89]), "+f"(d[90]), "+f"(d[91]), "+f"(d[92]), "+f"(d[93]), "+f"(d[94]), "+f"(d[95]), "+f"(d[96]), "+f"(d[97]), "+f"(d[98]), "+f"(d[99]), "+f"(d[100]), "+f"(d[101]), "+f"(d[102]), "+f"(d[103]), "+f"(d[104]), "+f"(d[105]), "+f"(d[106]), "+f"(d[107]), "+f"(d[108]), "+f"(d[109]), "+f"(d[110]), "+f"(d[111]), "+f"(d[112]), "+f"(d[113]), "+f"(d[114]), "+f"(d[115]), "+f"(d[116]), "+f"(d[117]), "+f"(d[118]), "+f"(d[119]), "+f"(d[120]), "+f"(d[121]), "+f"(d[122]), "+f"(d[123]), "+f"(d[124]), "+f"(d[125]), "+f"(d[126]), "+f"(d[127])
    : "r"(da), "r"(db));
  }
}
template<bool INIT> __device__ __forceinline__ void wgmma_n128_nn(float* d, uint32_t da, uint32_t db) {
  if constexpr (INIT) {
  asm volatile("{\n.reg .pred p;\n.reg .b64 da, db;\nsetp.ne.b32 p, 0, 0;\nmov.b64 da, {%64, 8};\nmov.b64 db, {%65, 8};\nwgmma.mma_async.sync.aligned.m64n128k16.f32.bf16.bf16 {%0, %1, %2, %3, %4, %5, %6, %7, %8, %9, %10, %11, %12, %13, %14, %15, %16, %17, %18, %19, %20, %21, %22, %23, %24, %25, %26, %27, %28, %29, %30, %31, %32, %33, %34, %35, %36, %37, %38, %39, %40, %41, %42, %43, %44, %45, %46, %47, %48, %49, %50, %51, %52, %53, %54, %55, %56, %57, %58, %59, %60, %61, %62, %63}, da, db, p, 1, 1, 0, 0;\n}\n"
    : "=f"(d[0]), "=f"(d[1]), "=f"(d[2]), "=f"(d[3]), "=f"(d[4]), "=f"(d[5]), "=f"(d[6]), "=f"(d[7]), "=f"(d[8]), "=f"(d[9]), "=f"(d[10]), "=f"(d[11]), "=f"(d[12]), "=f"(d[13]), "=f"(d[14]), "=f"(d[15]), "=f"(d[16]), "=f"(d[17]), "=f"(d[18]), "=f"(d[19]), "=f"(d[20]), "=f"(d[21]), "=f"(d[22]), "=f"(d[23]), "=f"(d[24]), "=f"(d[25]), "=f"(d[26]), "=f"(d[27]), "=f"(d[28]), "=f"(d[29]), "=f"(d[30]), "=f"(d[31]), "=f"(d[32]), "=f"(d[33]), "=f"(d[34]), "=f"(d[35]), "=f"(d[36]), "=f"(d[37]), "=f"(d[38]), "=f"(d[39]), "=f"(d[40]), "=f"(d[41]), "=f"(d[42]), "=f"(d[43]), "=f"(d[44]), "=f"(d[45]), "=f"(d[46]), "=f"(d[47]), "=f"(d[48]), "=f"(d[49]), "=f"(d[50]), "=f"(d[51]), "=f"(d[52]), "=f"(d[53]), "=f"(d[54]), "=f"(d[55]), "=f"(d[56]), "=f"(d[57]), "=f"(d[58]), "=f"(d[59]), "=f"(d[60]), "=f"(d[61]), "=f"(d[62]), "=f"(d[63])
    : "r"(da), "r"(db));
  } else {
  asm volatile("{\n.reg .pred p;\n.reg .b64 da, db;\nsetp.ne.b32 p, 1, 0;\nmov.b64 da, {%64, 8};\nmov.b64 db, {%65, 8};\nwgmma.mma_async.sync.aligned.m64n128k16.f32.bf16.bf16 {%0, %1, %2, %3, %4, %5, %6, %7, %8, %9, %10, %11, %12, %13, %14, %15, %16, %17, %18, %19, %20, %21, %22, %23, %24, %25, %26, %27, %28, %29, %30, %31, %32, %33, %34, %35, %36, %37, %38, %39, %40, %41, %42, %43, %44, %45, %46, %47, %48, %49, %50, %51, %52, %53, %54, %55, %56, %57, %58, %59, %60, %61, %62, %63}, da, db, p, 1, 1, 0, 0;\n}\n"
    : "+f"(d[0]), "+f"(d[1]), "+f"(d[2]), "+f"(d[3]), "+f"(d[4]), "+f"(d[5]), "+f"(d[6]), "+f"(d[7]), "+f"(d[8]), "+f"(d[9]), "+f"(d[10]), "+f"(d[11]), "+f"(d[12]), "+f"(d[13]), "+f"(d[14]), "+f"(d[15]), "+f"(d[16]), "+f"(d[17]), "+f"(d[18]), "+f"(d[19]), "+f"(d[20]), "+f"(d[21]), "+f"(d[22]), "+f"(d[23]), "+f"(d[24]), "+f"(d[25]), "+f"(d[26]), "+f"(d[27]), "+f"(d[28]), "+f"(d[29]), "+f"(d[30]), "+f"(d[31]), "+f"(d[32]), "+f"(d[33]), "+f"(d[34]), "+f"(d[35]), "+f"(d[36]), "+f"(d[37]), "+f"(d[38]), "+f"(d[39]), "+f"(d[40]), "+f"(d[41]), "+f"(d[42]), "+f"(d[43]), "+f"(d[44]), "+f"(d[45]), "+f"(d[46]), "+f"(d[47]), "+f"(d[48]), "+f"(d[49]), "+f"(d[50]), "+f"(d[51]), "+f"(d[52]), "+f"(d[53]), "+f"(d[54]), "+f"(d[55]), "+f"(d[56]), "+f"(d[57]), "+f"(d[58]), "+f"(d[59]), "+f"(d[60]), "+f"(d[61]), "+f"(d[62]), "+f"(d[63])
    : "r"(da), "r"(db));
  }
}
template<bool INIT> __device__ __forceinline__ void wgmma_n64_tt(float* d, uint32_t da, uint32_t db) {
  if constexpr (INIT) {
  asm volatile("{\n.reg .pred p;\n.reg .b64 da, db;\nsetp.ne.b32 p, 0, 0;\nmov.b64 da, {%32, 0x40000040};\nmov.b64 db, {%33, 0x40000040};\nwgmma.mma_async.sync.aligned.m64n64k16.f32.bf16.bf16 {%0, %1, %2, %3, %4, %5, %6, %7, %8, %9, %10, %11, %12, %13, %14, %15, %16, %17, %18, %19, %20, %21, %22, %23, %24, %25, %26, %27, %28, %29, %30, %31}, da, db, p, 1, 1, 1, 1;\n}\n"
    : "=f"(d[0]), "=f"(d[1]), "=f"(d[2]), "=f"(d[3]), "=f"(d[4]), "=f"(d[5]), "=f"(d[6]), "=f"(d[7]), "=f"(d[8]), "=f"(d[9]), "=f"(d[10]), "=f"(d[11]), "=f"(d[12]), "=f"(d[13]), "=f"(d[14]), "=f"(d[15]), "=f"(d[16]), "=f"(d[17]), "=f"(d[18]), "=f"(d[19]), "=f"(d[20]), "=f"(d[21]), "=f"(d[22]), "=f"(d[23]), "=f"(d[24]), "=f"(d[25]), "=f"(d[26]), "=f"(d[27]), "=f"(d[28]), "=f"(d[29]), "=f"(d[30]), "=f"(d[31])
    : "r"(da), "r"(db));
  } else {
  asm volatile("{\n.reg .pred p;\n.reg .b64 da, db;\nsetp.ne.b32 p, 1, 0;\nmov.b64 da, {%32, 0x40000040};\nmov.b64 db, {%33, 0x40000040};\nwgmma.mma_async.sync.aligned.m64n64k16.f32.bf16.bf16 {%0, %1, %2, %3, %4, %5, %6, %7, %8, %9, %10, %11, %12, %13, %14, %15, %16, %17, %18, %19, %20, %21, %22, %23, %24, %25, %26, %27, %28, %29, %30, %31}, da, db, p, 1, 1, 1, 1;\n}\n"
    : "+f"(d[0]), "+f"(d[1]), "+f"(d[2]), "+f"(d[3]), "+f"(d[4]), "+f"(d[5]), "+f"(d[6]), "+f"(d[7]), "+f"(d[8]), "+f"(d[9]), "+f"(d[10]), "+f"(d[11]), "+f"(d[12]), "+f"(d[13]), "+f"(d[14]), "+f"(d[15]), "+f"(d[16]), "+f"(d[17]), "+f"(d[18]), "+f"(d[19]), "+f"(d[20]), "+f"(d[21]), "+f"(d[22]), "+f"(d[23]), "+f"(d[24]), "+f"(d[25]), "+f"(d[26]), "+f"(d[27]), "+f"(d[28]), "+f"(d[29]), "+f"(d[30]), "+f"(d[31])
    : "r"(da), "r"(db));
  }
}
template<bool INIT> __device__ __forceinline__ void wgmma_n8_tn(float* d, uint32_t da, uint32_t db) {
  if constexpr (INIT) {
  asm volatile("{\n.reg .pred p;\n.reg .b64 da, db;\nsetp.ne.b32 p, 0, 0;\nmov.b64 da, {%4, 0x40000040};\nmov.b64 db, {%5, 8};\nwgmma.mma_async.sync.aligned.m64n8k16.f32.bf16.bf16 {%0, %1, %2, %3}, da, db, p, 1, 1, 1, 0;\n}\n"
    : "=f"(d[0]), "=f"(d[1]), "=f"(d[2]), "=f"(d[3])
    : "r"(da), "r"(db));
  } else {
  asm volatile("{\n.reg .pred p;\n.reg .b64 da, db;\nsetp.ne.b32 p, 1, 0;\nmov.b64 da, {%4, 0x40000040};\nmov.b64 db, {%5, 8};\nwgmma.mma_async.sync.aligned.m64n8k16.f32.bf16.bf16 {%0, %1, %2, %3}, da, db, p, 1, 1, 1, 0;\n}\n"
    : "+f"(d[0]), "+f"(d[1]), "+f"(d[2]), "+f"(d[3])
    : "r"(da), "r"(db));
  }
}
template<bool INIT> __device__ __forceinline__ void wgmma_n40_tf32(float* d, const uint32_t* a, uint32_t db) {
  if constexpr (INIT) {
  asm volatile("{\n.reg .pred p;\n.reg .b64 db;\nsetp.ne.b32 p, 0, 0;\nmov.b64 db, {%24, 0x40000040};\nwgmma.mma_async.sync.aligned.m64n40k8.f32.tf32.tf32 {%0, %1, %2, %3, %4, %5, %6, %7, %8, %9, %10, %11, %12, %13, %14, %15, %16, %17, %18, %19}, {%20, %21, %22, %23}, db, p, 1, 1;\n}\n"
    : "=f"(d[0]), "=f"(d[1]), "=f"(d[2]), "=f"(d[3]), "=f"(d[4]), "=f"(d[5]), "=f"(d[6]), "=f"(d[7]), "=f"(d[8]), "=f"(d[9]), "=f"(d[10]), "=f"(d[11]), "=f"(d[12]), "=f"(d[13]), "=f"(d[14]), "=f"(d[15]), "=f"(d[16]), "=f"(d[17]), "=f"(d[18]), "=f"(d[19])
    : "r"(a[0]), "r"(a[1]), "r"(a[2]), "r"(a[3]), "r"(db));
  } else {
  asm volatile("{\n.reg .pred p;\n.reg .b64 db;\nsetp.ne.b32 p, 1, 0;\nmov.b64 db, {%24, 0x40000040};\nwgmma.mma_async.sync.aligned.m64n40k8.f32.tf32.tf32 {%0, %1, %2, %3, %4, %5, %6, %7, %8, %9, %10, %11, %12, %13, %14, %15, %16, %17, %18, %19}, {%20, %21, %22, %23}, db, p, 1, 1;\n}\n"
    : "+f"(d[0]), "+f"(d[1]), "+f"(d[2]), "+f"(d[3]), "+f"(d[4]), "+f"(d[5]), "+f"(d[6]), "+f"(d[7]), "+f"(d[8]), "+f"(d[9]), "+f"(d[10]), "+f"(d[11]), "+f"(d[12]), "+f"(d[13]), "+f"(d[14]), "+f"(d[15]), "+f"(d[16]), "+f"(d[17]), "+f"(d[18]), "+f"(d[19])
    : "r"(a[0]), "r"(a[1]), "r"(a[2]), "r"(a[3]), "r"(db));
  }
}


__device__ __forceinline__ void quad_transpose(uint32_t& r0, uint32_t& r1, uint32_t& r2, uint32_t& r3, int c) {
  bool o1 = c & 1, o2 = c & 2;
  uint32_t t0 = o1 ? r0 : r1, t1 = o1 ? r2 : r3;
  t0 = __shfl_xor_sync(~0u, t0, 1); t1 = __shfl_xor_sync(~0u, t1, 1);
  if (o1) { r0 = t0; r2 = t1; } else { r1 = t0; r3 = t1; }
  t0 = o2 ? r0 : r2; t1 = o2 ? r1 : r3;
  t0 = __shfl_xor_sync(~0u, t0, 2); t1 = __shfl_xor_sync(~0u, t1, 2);
  if (o2) { r0 = t0; r1 = t1; } else { r2 = t0; r3 = t1; }
}

__device__ __forceinline__ bool own_tile(int T) { return (0x0D0Cu >> T) & 1; }
__device__ __forceinline__ bool wide_tile(int T) { return (0x3939u >> T) & 1; }

template<int V> struct IntC { static constexpr int value = V; };

__device__ __forceinline__ const CUtensorMap* tile_info(const Params& prm, int T, int j, int rank, int& col) {
  const int tile = T & 7;
  col = 128 * j + 64 * rank;
  if (tile == 0) col = 1024 + 1024 * rank + 128 * j;
  if (tile < 2) return T < 8 ? &prm.wqkv_n : &prm.wqkv_p;
  if (tile == 2) return &prm.wo_p;
  if (tile == 7) return &prm.wd_p;
  col = 448 * j + 128 * (tile - 3);
  return rank ? &prm.wu_p : &prm.wg_p;
}

__device__ __forceinline__ void split3(float x, uint32_t& a, uint32_t& b, uint32_t& c) {
  a = pack_bf16(0.f, x); x -= __uint_as_float(a);
  b = pack_bf16(0.f, x); x -= __uint_as_float(b);
  c = pack_bf16(0.f, x);
}
__device__ __forceinline__ void cs_operand(uint32_t addr, float cs) {
  uint32_t c1, c2, c3;
  split3(cs, c1, c2, c3);
  sts_v4(addr, make_uint4(c2 | (c1 >> 16), c3 | (c1 >> 16), c1 | (c2 >> 16), 0));
}
__device__ __forceinline__ void tile_stats(const uint32_t* P, float2 (*st)[8], int row, int j, int lane) {
  float s[2][4] = {}, q[2][2][4] = {};
#pragma unroll
  for (int i = 0; i < 8; i++) {
    const uint32_t* p = P + 4 * i;
    float* d = s[i & 1];
    asm("mma.sync.aligned.m16n8k16.row.col.f32.bf16.bf16.f32 {%0, %1, %2, %3}, {%4, %5, %6, %7}, {%8, %8}, {%0, %1, %2, %3};"
        : "+f"(d[0]), "+f"(d[1]), "+f"(d[2]), "+f"(d[3]) : "r"(p[0]), "r"(p[1]), "r"(p[2]), "r"(p[3]), "r"(0x3F803F80u));
#pragma unroll
    for (int t = 0; t < 4; t++) {
      float* e = q[i & 1][t & 1];
      asm("mma.sync.aligned.m16n8k8.row.col.f32.bf16.bf16.f32 {%0, %1, %2, %3}, {%4, %5}, {%6}, {%0, %1, %2, %3};"
          : "+f"(e[0]), "+f"(e[1]), "+f"(e[2]), "+f"(e[3]) : "r"(p[t & 2]), "r"(p[(t & 2) + 1]), "r"(p[t]));
    }
  }
  const bool odd = lane & 4, diag = (lane & 3) == (lane >> 3);
#pragma unroll
  for (int hf = 0; hf < 2; hf++) {
    const float sum = s[hf][0] + s[hf][2], sq = odd ? q[hf][0][1] + q[hf][1][3] : q[hf][0][0] + q[hf][1][2];
    st_f2_if(&st[row + 8 * hf][j], sum * (1.f / 128.f), fmaxf(sq - sum * sum * (1.f / 128.f), 0.f), diag);
  }
}

__device__ __forceinline__ void pack_half(const float* acc, uint32_t* PK) {
#pragma unroll
  for (int b = 0; b < 16; b++) {
    const int o = ((b >> 2) & 1) * 16 + (b >> 3) * 4 + (b & 3);
    PK[o] = pack_bf16(acc[4 * b], acc[4 * b + 1]);
    PK[o + 8] = pack_bf16(acc[4 * b + 2], acc[4 * b + 3]);
  }
}
template<int N> __device__ __forceinline__ void move_down(uint32_t* PK) {
#pragma unroll
  for (int q = 0; q < N; q++) asm volatile("mov.b32 %0, %1;" : "=r"(PK[q]) : "r"(PK[q + N]));
}
__device__ __forceinline__ void next_unit(uint32_t* PK, int u) {
  if (!(u & 1)) move_down<8>(PK); else if (!(u & 2)) move_down<16>(PK); else move_down<32>(PK);
}
__device__ __forceinline__ void lds_v4(uint32_t* v, uint32_t addr) {
  asm volatile("ld.shared.v4.u32 {%0, %1, %2, %3}, [%4];" : "=r"(v[0]), "=r"(v[1]), "=r"(v[2]), "=r"(v[3]) : "r"(addr) : "memory");
}
__device__ __forceinline__ void lds_tile(uint32_t* P, uint32_t b0, uint32_t b1, uint32_t ioff) {
#pragma unroll
  for (int q = 0; q < 8; q++) lds_v4(P + 4 * q, ((q >> 2) ? b1 : b0) + (q & 1) * 1024 + (ioff ^ ((q & 2) * 32)));
}
__device__ __forceinline__ void transpose_all(uint32_t* P, int c) {
#pragma unroll
  for (int q = 0; q < 8; q++) quad_transpose(P[4 * q], P[4 * q + 1], P[4 * q + 2], P[4 * q + 3], c);
}
__device__ __forceinline__ void add_residual(uint32_t* P, const float* acc) {
#pragma unroll
  for (int b = 0; b < 16; b++) {
    const int i0 = (b >> 2) * 8 + (b & 3), i1 = i0 + 4;
    P[i0] = P[32 + i0] = hadd2(P[32 + i0], pack_bf16(acc[4 * b], acc[4 * b + 1]));
    P[i1] = P[32 + i1] = hadd2(P[32 + i1], pack_bf16(acc[4 * b + 2], acc[4 * b + 3]));
  }
}
__device__ __forceinline__ float phi_s(float raw, float rstd, float rl2) { return fmaxf(fmaf(raw, rstd, 1.000001f), __saturatef(ex2f(raw * rl2) + 1e-6f)); }

template<bool HELPER>
__device__ __forceinline__ void colsum_warp(const Params& prm, uint32_t sb, uint32_t cbar, int id, int m, int j, int lane, uint32_t epoch) {
  const bool lead = elect_one();
  const int nbox = HELPER ? (id < 16 ? 48 : 40) : 2;
  float acc[8] = {};
  auto unit = [&](int b, int& col, int& kb, int& mat) {
    const int un = (b >> 3) * 48 + id, ch = un >> 1;
    kb = (un & 1) * 8 + (b & 7);
    if (ch < 16) col = ch * 64;
    else { const int q = ch - 16; mat = 1 + (q & 1); col = q < 96 ? 448 * ((q >> 2) & 7) + 128 * (q >> 5) + 32 * (q & 2) : 448 * ((q - 96) >> 1) + 384; }
  };
#pragma unroll 1
  for (int it = 0; it < 2 * nbox + 1; it++) {
    const int bx = it >> 1, k = it == 0 ? 0 : 1 - (it & 1);
    const int b = it == 0 ? 0 : k ? bx - 1 : bx + 1;
    if (b >= nbox) continue;
    int col, kb = m, mat = 0;
    if (HELPER) {
      unit(b, col, kb, mat);
    } else {
      col = 1024 + id * 1024 + 128 * j + b * 64;
    }
    const uint32_t sl = b & 1;
    if (k == 0) {
      if (lead) {
        mbar_expect_tx(cbar + 8 * sl, 8192);
        tma_5d(sb + sl * 8192, mat == 0 ? &prm.wqkv_n : mat == 1 ? &prm.wg_p : &prm.wu_p, cbar + 8 * sl, col, kb * 2);
      }
    } else {
      mbar_wait(cbar + 8 * sl, (b >> 1) & 1);
      const uint32_t ad = sb + sl * 8192 + (lane >> 3) * 128;
#pragma unroll 2
      for (int q = 0; q < 8; q++) {
        uint4 v, w;
        asm volatile("ld.shared.v4.u32 {%0, %1, %2, %3}, [%4];" : "=r"(v.x), "=r"(v.y), "=r"(v.z), "=r"(v.w) : "r"(ad + q * 1024 + (((lane & 7) ^ (lane >> 3)) << 4)) : "memory");
        asm volatile("ld.shared.v4.u32 {%0, %1, %2, %3}, [%4];" : "=r"(w.x), "=r"(w.y), "=r"(w.z), "=r"(w.w) : "r"(ad + q * 1024 + 512 + (((lane & 7) ^ (lane >> 3) ^ 4) << 4)) : "memory");
        acc[0] += bf_lo(v.x) + bf_lo(w.x); acc[1] += bf_hi(v.x) + bf_hi(w.x); acc[2] += bf_lo(v.y) + bf_lo(w.y); acc[3] += bf_hi(v.y) + bf_hi(w.y);
        acc[4] += bf_lo(v.z) + bf_lo(w.z); acc[5] += bf_hi(v.z) + bf_hi(w.z); acc[6] += bf_lo(v.w) + bf_lo(w.w); acc[7] += bf_hi(v.w) + bf_hi(w.w);
      }
      __syncwarp();
      if (!HELPER || (b & 7) == 7) {
#pragma unroll
        for (int q = 0; q < 8; q++) { acc[q] += __shfl_xor_sync(~0u, acc[q], 8); acc[q] += __shfl_xor_sync(~0u, acc[q], 16); }
        float* dst = &prm.sc->cs[epoch & 1][(mat == 0 ? 0 : mat == 1 ? 3072 : 3072 + F_) + col + 8 * (lane & 7)];
        if (lane < 8) { red_add_v4(dst, acc[0], acc[1], acc[2], acc[3]); red_add_v4(dst + 4, acc[4], acc[5], acc[6], acc[7]); }
#pragma unroll
        for (int q = 0; q < 8; q++) acc[q] = 0.f;
        if (b == nbox - 1 || (HELPER && (b < 16 || b == 31))) {
          __syncwarp();
          if (lead) { fence_gpu(); red_add_u32(&prm.sc->cscnt[HELPER ? (b > 31 ? 11 : 8 + ((b + 1) >> 4)) : j][0], 1); }
        }
      }
    }
  }
}


__global__ void __launch_bounds__(384, 1) fused_kernel(const __grid_constant__ Params prm) {
  extern __shared__ __align__(1024) uint8_t smem_raw[];
#define SMEM_ADDRS \
  const uint32_t sbase = __shfl_sync(~0u, smem_u32(smem_raw), 0); \
  const uint32_t full = sbase + OFF_BAR, empty = full + 64; \
  const uint32_t bar_kvdone = full + 128, bar_kvready = full + 136, bar_sig = full + 144; \
  const uint32_t bar_sig2 = full + 160, bar_cs = full + 176, bar_res = full + 216, bar_ln = full + 256;
  const int warp = __shfl_sync(~0u, threadIdx.x >> 5, 0);
  const bool helper = prm.role[blockIdx.x >> 1] >= 64;
#define ROLE_IDS \
  int bid; asm volatile("mov.u32 %0, %%ctaid.x;" : "=r"(bid)); \
  const int rank = bid & 1, role = prm.role[bid >> 1], mp = role & 7, j = role >> 3; \
  const int m = mp * 2 + rank, cta = m * 8 + j;

  {
  SMEM_ADDRS
  ROLE_IDS
  if (elect_one()) {
    if (!helper) {
      const int q = m >> 2, kb = 2 * ((q >> 1) + ((q >> 1) >= j)) + (q & 1);
      if (warp == 10) asm volatile("cp.async.bulk.prefetch.tensor.2d.L2.global.tile [%0, {%1, %2}];" :: "l"((uint64_t)&prm.x), "r"(j * 64), "r"(m * 128) : "memory");
      if (warp == 11) tma_5d_prefetch(&prm.wqkv_n, 1024 + 1024 * rank + 128 * j + (m & 2) * 32, kb * 2);
    }
#pragma unroll 1
    for (int t = warp; t < 33; t += 12) mbar_init(full + 8 * t, helper ? 1 : t == 16 ? 8 : 1 + 3 * (int)((0x3CFF00ull >> t) & 1));
    asm volatile("fence.mbarrier_init.release.cluster;" ::: "memory");
  }
  }
  __syncwarp();
  asm volatile("barrier.cluster.arrive.relaxed.aligned;" ::: "memory");

  if (helper) {
    SMEM_ADDRS
    cluster_wait();
    colsum_warp<true>(prm, sbase + warp * 16384, full + warp * 16, warp * 4 + (blockIdx.x & 3), 0, 0, lane_id(), load_epoch());
  } else if (warp >= 4) {
    asm volatile("setmaxnreg.inc.sync.aligned.u32 232;");
    SMEM_ADDRS
    ROLE_IDS
    const int lane = lane_id();
    const int cw = (warp >> 2) - 1, w4 = warp & 3, g = lane >> 2, c = lane & 3;
    uint32_t PK[64];
    if (w4 < 2) sts_u32(sbase + OFF_ONES + (w4 * 32 + lane) * 4, 0x3F803F80u);
    cluster_wait();

    const bool relt = w4 == 0 && lane < 2;
    const uint32_t dones = make_desc(sbase + OFF_ONES, 128);
    {
      const int rloc = cw * 64 + w4 * 16 + g;
      const uint32_t ioff = rloc * 128 + ((c ^ g) << 4);
      const uint32_t da0 = make_desc(sbase + cw * 8192, 16), db0 = make_desc(sbase + SLOT, 8192);
      const uint32_t stg = sbase + OFF_STG + cw * 16384;
      const uint32_t rempty = mapa(empty, lane & 1);
      uint32_t n = 0, pos = 0;
      bool ok = false;
      float rstd0, rstd1;
#pragma unroll 1
      for (int T = 0; T < 16; T++) {
        const int layer = T >> 3, tile = T & 7;
        if (tile == 1) continue;
        const bool wide = wide_tile(T), own = own_tile(T);
        const int nsteps = tile == 7 ? 56 : 16;
        const bool lnin = tile == 0 || tile == 3;
        float2 (*st)[8] = prm.sc->rb[m].stats[layer * 2 + (tile != 0)];
        if (tile == 3) { pos += 2048; if (pos >= NSLOT * 1024) pos -= NSLOT * 1024; }
        auto run = [&](auto WIDE_) {
          constexpr bool WIDE = decltype(WIDE_)::value;
          float acc[WIDE ? 128 : 64];
          auto kstepg = [&](auto W_, auto FIRST_, float* acc, auto&& hook) {
            constexpr bool FIRST = decltype(FIRST_)::value, WIDE = decltype(W_)::value;
            if (!ok) mbar_wait(full + 8 * (n & 7), (n >> 3) & 1);
            const uint32_t da = da0 + pos, db = db0 + pos;
            n++;
            pos += WIDE ? 3072 : 2048; if (pos >= NSLOT * 1024) pos -= NSLOT * 1024;
            wgmma_fence();
#pragma unroll
            for (int kk = 0; kk < 4; kk++) {
              if (FIRST && kk == 0) { if constexpr (WIDE) wgmma_n256_ss<true>(acc, da, db); else wgmma_n128_ss<true>(acc, da, db); }
              else { if constexpr (WIDE) wgmma_n256_ss<false>(acc, da + kk * 2, db + kk * 128); else wgmma_n128_ss<false>(acc, da + kk * 2, db + kk * 128); }
              if (kk == 1) {
                if constexpr (!FIRST) {
                  wgmma_commit();
                  wgmma_wait<1>();
                  mbar_arrive_remote_if(rempty + 8 * ((n - 2) & 7), relt);
                }
                ok = mbar_test(full + 8 * (n & 7), (n >> 3) & 1);
              }
              if (kk == 3) wgmma_commit();
              hook(kk);
            }
          };
          auto kstep = [&](auto FIRST_, auto&& hook) { kstepg(WIDE_, FIRST_, acc, hook); };
          auto nohook = [](int) {};
          uint8_t* img = prm.sc->rb[m].act[WIDE ? (tile == 0 ? 2 : 1) : 0] + 2 * j * SLOT;
          if (own) {
            auto publish = [&]() {
#pragma unroll
            for (int q = WIDE ? 0 : 4; q < (WIDE ? 4 : 8); q++)
              *(uint4*)(img + (q >> 2) * SLOT + (q & 1) * 1024 + (ioff ^ ((q & 2) * 32))) = make_uint4(PK[4 * q], PK[4 * q + 1], PK[4 * q + 2], PK[4 * q + 3]);
            __syncwarp();
            mbar_arrive_if((WIDE ? bar_sig : bar_sig2) + 8 * cw, lane == 0);
            };
            if (WIDE) publish();
            mbar_wait(full + 8 * (n & 7), (n >> 3) & 1);
            if (WIDE) tile_stats(PK, st, rloc, j, lane);
            mbar_wait(full + 8 * ((n + 1) & 7), ((n + 1) >> 3) & 1);
            ok = true;
            uint32_t p1 = pos + (WIDE ? 3072 : 2048); if (p1 >= NSLOT * 1024) p1 -= NSLOT * 1024;
#pragma unroll
            for (int q = 0; q < 8; q++)
              sts_v4(sbase + ((q >> 2) ? p1 : pos) * 16 + (q & 1) * 1024 + (ioff ^ ((q & 2) * 32)), make_uint4(PK[4 * q], PK[4 * q + 1], PK[4 * q + 2], PK[4 * q + 3]));
            fence_async_smem();
            wg_bar(1 + cw);
            if (!WIDE) publish();
          }
          kstep(IntC<1>{}, nohook);
          int i = 1;
          {
            if (tile >= 4) {
              uint32_t* t = PK;
              const int nu = tile == 6 ? 4 : 8;
              uint8_t* hb = prm.sc->rb[m].h + ((tile - 4) * 16 + (tile == 7 ? j : 2 * j)) * SLOT;
              const int hb2 = tile == 7 ? (j - 15) * (int)SLOT : SLOT;
#pragma unroll 1
              for (int u = 0; u < nu; u++) {
                const float rstd = (u & 1) ? rstd1 : rstd0;
                const float ke = rstd * -1.4426950408889634f, iv = rcpf(rstd * rstd);
                auto glu = [&](int q) {
                  float s0 = rcpf(fmaf(ex2f(bf_lo(t[q]) * ke), iv, iv)), s1 = rcpf(fmaf(ex2f(bf_hi(t[q]) * ke), iv, iv));
                  t[q] = hmul2(hmul2(t[q], t[4 + q]), pack_bf16(s0, s1));
                };
                if constexpr (WIDE) kstep(IntC<0>{}, glu);
                else {
                  kstep(IntC<0>{}, [&](int q) { if (q & 1) glu(q >> 1); });
                  kstep(IntC<0>{}, [&](int q) { if (q & 1) glu(2 + (q >> 1)); });
                  i++;
                }
                *(uint4*)(hb + (u >> 2) * hb2 + (u & 1) * 1024 + (ioff ^ ((u & 2) * 32))) = make_uint4(t[0], t[1], t[2], t[3]);
                next_unit(PK, u);
                i++;
              }
              __syncwarp();
              mbar_arrive_if(bar_sig + 8 * cw, lane == 0);
            }
          }
          int stop = tile == 7 ? 24 + 2 * cw : T ? (WIDE ? 4 : 2) : 5;
#pragma unroll 1
          for (int seg = 0; seg < 3; seg++) {
#pragma unroll 1
            for (; i < stop; i++) kstep(IntC<0>{}, nohook);
            if (seg == 0) {
              if (!WIDE && tile == 7) {
                mbar_wait(bar_res, layer);
                lds_tile(PK + 32, sbase + OFF_STG, sbase + OFF_STG + SLOT, ioff);
              }
              if (WIDE && own) {
#pragma unroll
                for (int q = 4; q < 8; q++)
                  *(uint4*)(img + SLOT + (q & 1) * 1024 + (ioff ^ ((q & 2) * 32))) = make_uint4(PK[4 * q], PK[4 * q + 1], PK[4 * q + 2], PK[4 * q + 3]);
              }
              if (WIDE && lnin) {
                if (T == 0) {
                  mbar_wait(full + 40, 0);
                  const int ln = lane_id();
#pragma unroll
                  for (int q = 0; q < 8; q++)
                    asm volatile("ldmatrix.sync.aligned.m8n8.x4.shared.b16 {%0, %1, %2, %3}, [%4];" : "=r"(PK[32 + 4 * q]), "=r"(PK[33 + 4 * q]), "=r"(PK[34 + 4 * q]), "=r"(PK[35 + 4 * q])
                                 : "r"(sbase + (q >> 2) * 3 * SLOT + (cw * 64 + w4 * 16 + (q & 1) * 8 + (ln & 7)) * 128 + ((((q & 2) * 2 + (ln >> 3)) ^ (ln & 7)) << 4)) : "memory");
                  tile_stats(PK + 32, st, rloc, j, lane);
                }
                __syncwarp();
                mbar_arrive_if(bar_sig2 + 8 * cw, lane == 0);
              }
              stop = nsteps - (T == 15 ? 4 : 1);
            } else {
              if (seg == 1) {
                if (WIDE && lnin) {
                  mbar_wait(bar_ln, tile != 0);
                  const uint32_t r0 = lds_u32(sbase + OFF_LN + rloc * 16 + 12), r1 = lds_u32(sbase + OFF_LN + rloc * 16 + 140);
                  rstd0 = bf_lo(r0) + bf_hi(r0); rstd1 = bf_lo(r1) + bf_hi(r1);
                }
                if (WIDE) mbar_wait(bar_cs + 8 * (tile - (tile > 2)), layer);
              }
              if (seg == 1 && cw == 1) asm volatile("bar.sync 3, 256;" ::: "memory");
              stop = nsteps;
            }
          }
          if (WIDE || tile == 6) {
            const uint32_t dc = make_desc(sbase + (tile == 0 ? OFF_CSKV : OFF_CSGU + (tile - 3) * 4096), 0);
            wgmma_fence();
            if constexpr (WIDE) wgmma_n256_nn<false>(acc, make_desc(sbase + OFF_LN + cw * 1024, 0), dc); else wgmma_n128_nn<false>(acc, make_desc(sbase + OFF_LN + cw * 1024, 0), dc);
            wgmma_commit();
          }
          if (cw == 0) asm volatile("bar.arrive 3, 256;" ::: "memory");
        wgmma_wait<0>();
        mbar_arrive_remote_if(rempty + 8 * ((n - 1) & 7), relt);
        if (!WIDE && (tile == 2 || tile == 7)) add_residual(PK, acc);
        else if (WIDE && tile == 0) {
          const float l0 = rstd0 * 1.4426950408889634f, l1 = rstd1 * 1.4426950408889634f;
          const uint32_t sta = stg + (w4 * 16 + ((lane >> 3) & 1) * 8 + (lane & 7)) * 128, da = make_desc(stg, 8192);
          float kv[2][32], z[2][4];
          if (cw == 0) asm volatile("bar.arrive 4, 256;" ::: "memory");
#pragma unroll
          for (int r = 0; r < 2; r++) {
            uint32_t* t = PK;
#pragma unroll
            for (int b = 0; b < 16; b++) {
              const float* a = acc + (WIDE ? 64 * r : 0) + 4 * b;
              const float v0 = a[0], v1 = a[1], v2 = a[2], v3 = a[3];
              if (b < 8) { t[2 * b] = pack_bf16(phi_s(v0, rstd0, l0), phi_s(v1, rstd0, l0)); t[2 * b + 1] = pack_bf16(phi_s(v2, rstd1, l1), phi_s(v3, rstd1, l1)); }
              else { t[2 * b] = pack_bf16(v0 * rstd0, v1 * rstd0); t[2 * b + 1] = pack_bf16(v2 * rstd1, v3 * rstd1); }
            }
            if (r) { wgmma_wait<0>(); wg_bar(1 + cw); }
            else if (cw == 1) asm volatile("bar.sync 4, 256;" ::: "memory");
#pragma unroll
            for (int b = 0; b < 16; b += 2)
              stmatrix_x4(sta + (b >> 3) * 8192 + ((((b & 7) + (lane >> 4)) ^ (lane & 7)) << 4), t[2 * b], t[2 * b + 1], t[2 * b + 2], t[2 * b + 3]);
            fence_async_smem();
            wg_bar(1 + cw);
            wgmma_fence();
            wgmma_n64_tt<true>(kv[r], da + 512, da);
            wgmma_n8_tn<true>(z[r], da, dones);
#pragma unroll
            for (int kk = 1; kk < 4; kk++) {
              wgmma_n64_tt<false>(kv[r], da + 512 + kk * 128, da + kk * 128);
              wgmma_n8_tn<false>(z[r], da + kk * 128, dones);
            }
            wgmma_commit();
          }
          float aq[64];
          auto qstep = [&]() { kstepg(IntC<0>{}, IntC<0>{}, aq, nohook); };
          kstepg(IntC<0>{}, IntC<1>{}, aq, nohook);
          wgmma_wait<1>();
          wg_bar(1 + cw);
#pragma unroll
          for (int q = 0; q < 32; q++) asm volatile("" : "+f"(kv[0][q]), "+f"(kv[1][q]));
          const uint32_t kb = stg + (w4 * 16 + g) * 128 + c * 4;
          float* zd = &prm.sc->kv[lds_u32(full + 480) & 1][layer][j][4096 + (w4 >> 1) * 32 + (w4 & 1) * 16 + (g & 1) * 4 + (g >> 1)];
          uint32_t keep[16], send[16];
#pragma unroll
          for (int q = 0; q < 16; q++) {
            const float v0 = w4 >= 2 ? kv[0][16 + q] : kv[0][q], v1 = w4 >= 2 ? kv[1][16 + q] : kv[1][q];
            keep[q] = __float_as_uint(cw ? v1 : v0); send[q] = __float_as_uint(cw ? v0 : v1);
          }
          const uint32_t xo = (w4 * 32 + lane) * 16;
#pragma unroll
          for (int q = 0; q < 4; q++) sts_v4(stg + xo + q * 2048, make_uint4(send[4 * q], send[4 * q + 1], send[4 * q + 2], send[4 * q + 3]));
#pragma unroll
          for (int r = 0; r < 2; r++) { red_add_f32_if(zd + 64 * r, z[r][0], c == 0); red_add_f32_if(zd + 64 * r + 8, z[r][2], c == 0); }
          qstep();
          asm volatile("bar.sync 5, 256;" ::: "memory");
#pragma unroll
          for (int q = 0; q < 4; q++) lds_v4(send + 4 * q, sbase + OFF_STG + (cw ^ 1) * 16384 + xo + q * 2048);
#pragma unroll
          for (int q = 0; q < 16; q++)
            sts_u32(kb + 8192 + (q & 2) * 512 + ((((q >> 2) * 2 + (q & 1)) ^ g) << 4), __float_as_uint(__uint_as_float(keep[q]) + __uint_as_float(send[q])));
          fence_async_smem();
          __syncwarp();
          mbar_arrive_if(bar_kvdone, lane == 0);
#pragma unroll 1
          for (int s2 = 0; s2 < 2; s2++) {
#pragma unroll 1
            for (int q = s2 ? 15 : 2; q < 15 + s2; q++) qstep();
            if (s2 == 0) {
              mbar_wait(bar_cs + 8, layer);
              if (cw == 1) asm volatile("bar.sync 3, 256;" ::: "memory");
            }
          }
          wgmma_fence();
          wgmma_n128_nn<false>(aq, make_desc(sbase + OFF_LN + cw * 1024, 0), make_desc(sbase + OFF_CSQ, 0));
          wgmma_commit();
          if (cw == 0) asm volatile("bar.arrive 3, 256;" ::: "memory");
          wgmma_wait<0>();
          mbar_arrive_remote_if(rempty + 8 * ((n - 1) & 7), relt);
          img = prm.sc->rb[m].act[0] + 2 * j * SLOT;
#pragma unroll
          for (int hp = 0; hp < 2; hp++) {
            uint32_t A[32];
#pragma unroll
            for (int b = 0; b < 8; b++) {
              const float* a = aq + 32 * hp + 4 * b;
              A[4 * b] = __float_as_uint(phi_s(a[0], rstd0, l0));
              A[4 * b + 1] = __float_as_uint(phi_s(a[2], rstd1, l1));
              A[4 * b + 2] = __float_as_uint(phi_s(a[1], rstd0, l0));
              A[4 * b + 3] = __float_as_uint(phi_s(a[3], rstd1, l1));
            }
            mbar_wait(bar_kvready, layer);
            float num[2][20];
            wgmma_fence();
#pragma unroll
            for (int ks = 0; ks < 4; ks++) {
#pragma unroll
              for (int hh = 0; hh < 2; hh++) {
                const uint32_t db = make_desc(sbase + OFF_STG + (2 * hp + hh) * 5120, 16) + 2 * ks;
                if (ks == 0) wgmma_n40_tf32<true>(num[hh], A + 16 * hh, db); else wgmma_n40_tf32<false>(num[hh], A + 16 * hh + 4 * ks, db);
              }
            }
            wgmma_commit();
            wgmma_wait<0>();
#pragma unroll
            for (int hh = 0; hh < 2; hh++) {
              const float* nm = num[hh];
              const float r0 = rcpf(__shfl_sync(~0u, nm[16], 0, 4) + 1e-6f), r1 = rcpf(__shfl_sync(~0u, nm[18], 0, 4) + 1e-6f);
#pragma unroll
              for (int b = 0; b < 4; b++) {
                PK[16 * hp + 8 * hh + b] = pack_bf16(nm[4 * b] * r0, nm[4 * b + 1] * r0);
                PK[16 * hp + 8 * hh + 4 + b] = pack_bf16(nm[4 * b + 2] * r1, nm[4 * b + 3] * r1);
              }
            }
            if (hp == 0) {
#pragma unroll
              for (int q = 0; q < 4; q++)
                *(uint4*)(img + (q & 1) * 1024 + (ioff ^ ((q & 2) * 32))) = make_uint4(PK[4 * q], PK[4 * q + 1], PK[4 * q + 2], PK[4 * q + 3]);
              __syncwarp();
              mbar_arrive_if(bar_sig + 8 * cw, lane == 0);
              mbar_wait(bar_kvready, layer);
            }
          }
        } else {
          pack_half(acc, PK);
          if constexpr (WIDE) pack_half(acc + 64, PK + 32);
        }
        };
        if (wide) run(IntC<1>{}); else run(IntC<0>{});
      }
      asm volatile("barrier.cluster.arrive.relaxed.aligned;" ::: "memory");
      transpose_all(PK, c);
      const int l2 = lane_id();
      const uint32_t xoff = ((m * 128 + cw * 64 + w4 * 16 + (l2 >> 2)) * D_ + 128 * j + 8 * (l2 & 3)) * 2;
#pragma unroll
      for (int q = 0; q < 8; q++)
        *(uint4*)((uint8_t*)prm.out + xoff + (q >> 1) * 64 + (q & 1) * 16 * D_) = make_uint4(PK[4 * q], PK[4 * q + 1], PK[4 * q + 2], PK[4 * q + 3]);
      if (cta == 0 && threadIdx.x == 128) prm.sc->epoch = lds_u32(full + 480);
    }
  } else {
    asm volatile("setmaxnreg.dec.sync.aligned.u32 40;");
    SMEM_ADDRS
    const int lane = lane_id();
    if (__builtin_expect(warp < 2, 1)) {
      ROLE_IDS
      uint32_t epoch = 0;
      auto border = [&](int T, int i) {
        if (own_tile(T)) { const int e = i > 8, q = i - 2 - 7 * e; return i < 2 ? 2 * j + i : 2 * (q + (q >= j)) + e; }
        if (T == 0) { const int p = i >> 1, q = p - (p > 2); return 2 * (p == 2 ? j : q + (q >= j)) + (i & 1); }
        return i;
      };
      if (warp == 0) {
        uint32_t n = 0, dst = sbase + SLOT + rank * 8192;
        const uint32_t dend = dst + NSLOT * SLOT;
        const bool lead = elect_one();
#pragma unroll 1
        for (int T = 0; T < 16; T++) {
          const int tile = T & 7;
          const bool wide = wide_tile(T);
          const uint32_t adv = (wide ? 3 : 2) * SLOT, dfill = wide ? 0x34000000u : 0x56000000u;
          uint32_t dtab = tile == 0 ? 0x34343445u : tile == 3 ? 0x34343334u : wide ? 0x34343434u : (tile == 1 || tile == 6) ? 0x56554534u : 0x56565656u;
          if (tile == 3) { dst += 2 * SLOT; if (dst >= dend) dst -= NSLOT * SLOT; }
          int col;
          const CUtensorMap* map = tile_info(prm, T, j, rank, col);
#pragma unroll 1
          for (int p = 0; p < (tile == 7 ? 28 : 8); p++) {
            int k0, k1;
            if (tile == 7) { k0 = p < 24 ? 7 * (p & 7) + 2 * (p >> 3) : 14 * p - 330; k1 = k0 + (p < 24 ? 1 : 7); }
            else { k0 = border(T, 2 * p); k1 = border(T, 2 * p + 1); }
            const int X0 = n - (dtab & 15), X1 = n - ((dtab >> 4) & 15);
            dtab = (dtab >> 8) | dfill;
            const uint32_t fb = full + 8 * (n & 7), bytes = (own_tile(T) && p == 0) ? adv - SLOT : adv;
            uint32_t dst1 = dst + adv; if (dst1 >= dend) dst1 -= NSLOT * SLOT;
            if (n == 0) cluster_wait();
            if (n >= 4) mbar_wait(empty + 8 * (X0 & 7), (X0 >> 3) & 1);
            if (lead) {
              mbar_expect_tx(fb, bytes);
              tma_5d_mc(dst, map, fb, col, k0 * 2);
              if (wide) tma_5d_mc(dst + SLOT, map, fb, col + 64, k0 * 2);
            }
            if (n >= 4) mbar_wait(empty + 8 * (X1 & 7), (X1 >> 3) & 1);
            if (lead) {
              mbar_expect_tx(fb + 8, bytes);
              tma_5d_mc(dst1, map, fb + 8, col, k1 * 2);
              if (wide) tma_5d_mc(dst1 + SLOT, map, fb + 8, col + 64, k1 * 2);
            }
            n += 2;
            dst = dst1 + adv; if (dst >= dend) dst -= NSLOT * SLOT;
          }
        }
      } else {
        uint32_t ready = 0, n = 0, dst = sbase;
        const uint32_t dend = dst + NSLOT * SLOT;
        const bool lead = elect_one();
        cluster_wait();
#pragma unroll 1
        for (int T = 0; T < 16; T++) {
          const int layer = T >> 3, tile = T & 7;
          const bool wide = wide_tile(T), own = own_tile(T);
          const uint32_t adv = (wide ? 3 : 2) * SLOT, dfill = wide ? 0x40000000u : 0x60000000u;
          uint32_t dtab = tile == 0 ? 0x44444455u : tile == 3 ? 0x44444344u : wide ? 0x44444444u : (tile == 1 || tile == 6) ? 0x66655544u : 0x66666666u;
          if (tile == 3) dst += 2 * SLOT;
          const int kind = tile < 2 ? 3 : tile == 2 ? 0 : tile < 7 ? 1 : 2;
          const uint8_t* img = prm.sc->rb[m].act[0] + (kind ^ (kind >> 1)) * 16 * SLOT;
          const uint32_t* fl = &prm.sc->rb[m].flag[layer][kind][lane];
          if ((0x8Du >> tile) & 1) ready = 0;
          if (T == 1) epoch = load_epoch();
          int i = 0;
          if (own) { i = 2; n += 2; dst += 2 * adv; dtab = (dtab >> 8) | dfill | (dfill >> 4); }
          if (dst >= dend) dst -= NSLOT * SLOT;
          const int ab = border(T, lane);
          if (T < 2) {
#pragma unroll 1
            for (; i < 16; i++) {
              const int X = n - (dtab & 15);
              dtab = (dtab >> 4) | dfill;
              const int c0 = border(T, i) * 64;
              if (X >= 0) mbar_wait(empty + 8 * (X & 7), (X >> 3) & 1);
              if (lead) tma_2d(dst, &prm.x, full + 8 * (n & 7), c0, m * 128);
              n++; dst += adv; if (dst >= dend) dst -= NSLOT * SLOT;
            }
          } else {
            int blk = own ? (j ? 0 : 2) : 0;
            const int inc = own ? 2 : 1, skip = own ? j : -1;
            uint32_t ok = 0;
#pragma unroll 1
            for (; i < (tile == 7 ? 56 : 16); i++) {
              if (!(ok & 1)) {
                const int ii = (i & 32) + lane;
                const uint32_t need = tile == 7 ? (ii < 32 ? 1u << (ii >> 1) : ii < 48 ? 0x101u << (ii >> 1) : 1u << (ii - 24)) : ((ab & 1) ? 256u : 1u) << (ab >> 1);
                uint32_t tries = 0;
                while (!((ok = __ballot_sync(~0u, (ready & need) == need) >> (i & 31)) & 1)) {
                  ready = __ballot_sync(~0u, ld_acquire(fl) == epoch);
                  if (++tries > (1u << 20)) __trap();
                }
                fence_async_global();
              }
              ok >>= 1;
              const int X = n - (dtab & 15);
              dtab = (dtab >> 4) | dfill;
              mbar_wait(empty + 8 * (X & 7), (X >> 3) & 1);
              if (lead) bulk_load(dst, img + blk * SLOT, SLOT, full + 8 * (n & 7));
              blk += inc;
              if (own && blk >= 16) blk = 1;
              if ((blk >> 1) == skip) blk += 2;
              if (own && blk >= 16) blk = 1;
              n++; dst += adv; if (dst >= dend) dst -= NSLOT * SLOT;
            }
          }
        }
      }
    } else {
      const int w = warp - 2;
      ROLE_IDS
      cluster_wait();
      const uint32_t epoch = load_epoch();
      sts_u32(full + 480, epoch);
      mbar_wait(full, 0);
      colsum_warp<false>(prm, sbase + OFF_STG + w * 16384, full + 224 + w * 16, w, m, j, lane, epoch);
      {
        float* z = &prm.sc->kv[(epoch & 1) ^ 1][0][0][0] + (size_t)cta * 528;
        for (int i = w * 32 + lane; i < 132; i += 64) *(float4*)(z + i * 4) = make_float4(0.f, 0.f, 0.f, 0.f);
        if (w && lane < 20) *(float4*)&prm.sc->cs[(epoch & 1) ^ 1][cta * 80 + lane * 4] = make_float4(0.f, 0.f, 0.f, 0.f);
      }
      if (w == 0) {
        int pf = 1;
        uint32_t sigph = 0;
#pragma unroll 1
        for (int ev = 1; ev < 20; ev++) {
          const int layer = ev >= 10, e = ev - 10 * layer;
          const bool se = e < 6 && (e & 1);
          const uint32_t sb = se ? bar_sig2 : bar_sig, sp = (sigph >> se) & 1;
          const int kind = (0x2222110033ull >> (4 * e)) & 3, sub = (0x3210101010ull >> (4 * e)) & 3;
          uint32_t* f = &prm.sc->rb[m].flag[layer][kind][sub * 8 + j];
          mbar_wait(sb, sp); mbar_wait(sb + 8, sp);
          if (e == 9 && lane == 0) {
            mbar_expect_tx(bar_res, 2 * SLOT);
            bulk_load(sbase + OFF_STG, prm.sc->rb[m].act[1] + 2 * j * SLOT, 2 * SLOT, bar_res);
          }
          if (lane == 0) { fence_gpu(); st_relaxed(f, epoch); fence_async_global(); }
          sigph ^= 1 + se;
          const int hi = min(16, layer * 8 + (int)((0x9886544331ull >> (4 * e)) & 15));
#pragma unroll 1
          for (; pf < hi; pf++) {
            int col;
            const CUtensorMap* map = tile_info(prm, pf, j, rank, col);
#pragma unroll 1
            for (int kb = mp; kb < ((pf & 7) == 7 ? 56 : 16); kb += 8) {
              if (lane == 0) { tma_5d_prefetch(map, col, kb * 2); if (wide_tile(pf)) tma_5d_prefetch(map, col + 64, kb * 2); }
              __nanosleep(500);
            }
          }
          __syncwarp();
        }
      } else {
#pragma unroll 1
        for (int rr = 0; rr < 10; rr++) {
          const int layer = rr >= 5, r = rr - 5 * layer;
          const bool lnr = r == 0 || r == 2;
          if (r == 2) {
            mbar_wait(bar_sig2, layer ^ 1); mbar_wait(bar_sig2 + 8, layer ^ 1);
          }
          if (lnr) { mbar_wait(bar_sig2, layer); mbar_wait(bar_sig2 + 8, layer); }
          poll_eq(&prm.sc->cscnt[r ? 7 + r : j][0], epoch * (r ? 48 : 32));
          if (r == 1) {
            float* kvp = prm.sc->kv[epoch & 1][layer][j];
            const float4 cq = __ldcg((const float4*)&prm.sc->cs[epoch & 1][128 * j + 4 * lane]);
            mbar_wait(bar_kvdone, layer);
            if (lane == 0) {
              bulk_reduce_f32(kvp, sbase + OFF_STG + 8192, 8192);
              bulk_reduce_f32(kvp + 2048, sbase + OFF_STG + 24576, 8192);
              asm volatile("cp.async.bulk.commit_group;\ncp.async.bulk.wait_group 0;" ::: "memory");
              fence_gpu();
              red_add_u32(&prm.sc->kvcnt[layer][j][0], 1);
              mbar_expect_tx(bar_kvready, 16896);
            }
            __syncwarp();
            cs_operand(sbase + OFF_CSQ + lane * 64, cq.x); cs_operand(sbase + OFF_CSQ + lane * 64 + 16, cq.y);
            cs_operand(sbase + OFF_CSQ + lane * 64 + 32, cq.z); cs_operand(sbase + OFF_CSQ + lane * 64 + 48, cq.w);
          } else
          {
            const int q0 = r > 2 ? 4 * r - 8 : 0, nq = (0x64424 >> (4 * r)) & 15;
            const uint32_t cb = full + 248, tmp = sbase + OFF_STG + 24576;
            fence_async_global();
            if (lane == 0) mbar_expect_tx(cb, nq * 256);
            __syncwarp();
            if (lane < nq) bulk_load(tmp + lane * 256, &prm.sc->cs[epoch & 1][(r == 0 ? 1024 + 128 * j : r == 1 ? 128 * j : 3072 + 448 * j + 32 * q0)
                                                                            + (lane & 1) * (r == 0 ? 1024 : r == 1 ? 64 : F_) + (lane >> 1) * 64], 256, cb);
            mbar_wait(cb, r ? r & 1 : 1);
            const uint32_t ad = sbase + (r == 0 ? OFF_CSKV : r == 1 ? OFF_CSQ : OFF_CSGU) + q0 * 1024;
#pragma unroll 2
            for (int q = lane; q < 64 * nq; q += 32) {
              cs_operand(ad + q * 16, __uint_as_float(lds_u32(tmp + q * 4)));
            }
          }
          fence_async_smem();
          __syncwarp();
          if (lane == 0) mbar_arrive(bar_cs + 8 * r);
          if (lnr) {
            poll_eq(&prm.sc->rb[m].flag[layer][r ? 1 : 3][8 + (lane & 7)], epoch);
            __syncwarp();
            const uint32_t lb = full + 240;
            if (lane == 0) {
              fence_async_global();
              mbar_expect_tx(lb, 8192);
              bulk_load(sbase + OFF_STG + 16384, prm.sc->rb[m].stats[layer * 2 + (r >> 1)], 8192, lb);
            }
            mbar_wait(lb, 1 ^ (r >> 1));
#pragma unroll 1
            for (int q = 0; q < 4; q++) {
              float4 t0, t1, t2, t3;
              const uint32_t sp = sbase + OFF_STG + 16384 + (q * 32 + lane) * 64;
              lds_v4((uint32_t*)&t0, sp + ((lane << 3) & 48)); lds_v4((uint32_t*)&t1, sp + (((lane << 3) + 16) & 48));
              lds_v4((uint32_t*)&t2, sp + (((lane << 3) + 32) & 48)); lds_v4((uint32_t*)&t3, sp + (((lane << 3) + 48) & 48));
              const float mean = ((t0.x + t0.z) + (t1.x + t1.z) + (t2.x + t2.z) + (t3.x + t3.z)) * 0.125f;
              auto sq = [&](float v) { return (v - mean) * (v - mean); };
              const float m2 = (t0.y + t0.w) + (t1.y + t1.w) + (t2.y + t2.w) + (t3.y + t3.w)
                             + 128.f * (sq(t0.x) + sq(t0.z) + sq(t1.x) + sq(t1.z) + sq(t2.x) + sq(t2.z) + sq(t3.x) + sq(t3.z));
              uint32_t a1, a2, a3, r1, r2, r3;
              split3(-0.5f * mean, a1, a2, a3);
              split3(rsqrtf(m2 * (1.f / 1024.f) + 1e-5f), r1, r2, r3);
              sts_v4(sbase + OFF_LN + (q * 32 + lane) * 16, make_uint4(a1 | (a1 >> 16), a1 | (a2 >> 16), a3 | (a2 >> 16), r1 | (r2 >> 16)));
            }
            fence_async_smem();
            __syncwarp();
            if (lane == 0) mbar_arrive(bar_ln);
          }
          if (r == 1) {
            float* kvp = prm.sc->kv[epoch & 1][layer][j];
            poll_eq(&prm.sc->kvcnt[layer][j][0], epoch * 16);
            fence_async_global();
            if (lane < 8) bulk_load(sbase + OFF_STG + (lane & 3) * 5120 + (lane >> 2) * 4096, kvp + (lane < 4 ? lane * 1024 : 4096 + (lane & 3) * 32), lane < 4 ? 4096 : 128, bar_kvready);
            __syncwarp();
          }
        }
      }
    }
  }
  __syncwarp();
  if (helper || warp < 4) asm volatile("barrier.cluster.arrive.relaxed.aligned;" ::: "memory");
  cluster_wait();
}

typedef CUresult (*EncodeTiledFn)(CUtensorMap*, CUtensorMapDataType, cuuint32_t, void*, const cuuint64_t*, const cuuint64_t*, const cuuint32_t*, const cuuint32_t*,
                                  CUtensorMapInterleave, CUtensorMapSwizzle, CUtensorMapL2promotion, CUtensorMapFloatOOBfill);

void make_wmap(EncodeTiledFn enc, CUtensorMap* m, const void* ptr, uint64_t rows, uint64_t cols, bool perm) {
  uint64_t rs = cols * 2;
  cuuint64_t gd[5] = {cols, 2, 4, 4, rows / 32};
  cuuint64_t gs[4] = {rs, (perm ? 8 : 2) * rs, (perm ? 2 : 8) * rs, 32 * rs};
  cuuint32_t bd[5] = {64, 2, 4, 4, 2}, es[5] = {1, 1, 1, 1, 1};
  enc(m, CU_TENSOR_MAP_DATA_TYPE_BFLOAT16, 5, (void*)ptr, gd, gs, bd, es, CU_TENSOR_MAP_INTERLEAVE_NONE, CU_TENSOR_MAP_SWIZZLE_128B,
      CU_TENSOR_MAP_L2_PROMOTION_L2_256B, CU_TENSOR_MAP_FLOAT_OOB_FILL_NONE);
}

void make_2d(EncodeTiledFn enc, CUtensorMap* m, const void* ptr, uint64_t rows, uint64_t cols, uint32_t box_rows) {
  cuuint64_t gd[2] = {cols, rows}, gs[1] = {cols * 2}; cuuint32_t bd[2] = {64, box_rows}, es[2] = {1, 1};
  enc(m, CU_TENSOR_MAP_DATA_TYPE_BFLOAT16, 2, (void*)ptr, gd, gs, bd, es, CU_TENSOR_MAP_INTERLEAVE_NONE, CU_TENSOR_MAP_SWIZZLE_128B,
      CU_TENSOR_MAP_L2_PROMOTION_L2_256B, CU_TENSOR_MAP_FLOAT_OOB_FILL_NONE);
}

}

extern "C" void kernel_launch(void* const* d_in, const int* in_sizes, int n_in, void* d_out, int out_size) {
  const __nv_bfloat16* x = (const __nv_bfloat16*)d_in[0];
  const __nv_bfloat16* wqkv = (const __nv_bfloat16*)d_in[1];
  const __nv_bfloat16* wo = (const __nv_bfloat16*)d_in[2];
  const __nv_bfloat16* wg = (const __nv_bfloat16*)d_in[4];
  const __nv_bfloat16* wu = (const __nv_bfloat16*)d_in[5];
  const __nv_bfloat16* wd = (const __nv_bfloat16*)d_in[6];

  void* fn = nullptr; cudaDriverEntryPointQueryResult qr;
  cudaGetDriverEntryPoint("cuTensorMapEncodeTiled", &fn, cudaEnableDefault, &qr);
  EncodeTiledFn enc = (EncodeTiledFn)fn;
  Params prm;
  make_2d(enc, &prm.x, x, S_, D_, 128);
  make_wmap(enc, &prm.wqkv_n, wqkv, D_, 3 * D_, false);
  make_wmap(enc, &prm.wqkv_p, wqkv, D_, 3 * D_, true);
  make_wmap(enc, &prm.wo_p, wo, D_, D_, true);
  make_wmap(enc, &prm.wg_p, wg, D_, F_, true);
  make_wmap(enc, &prm.wu_p, wu, D_, F_, true);
  make_wmap(enc, &prm.wd_p, wd, F_, D_, true);
  prm.out = (__nv_bfloat16*)d_out;
  cudaGetSymbolAddress((void**)&prm.sc, g_scratch);
  prm.sc = (Scratch*)(((uintptr_t)prm.sc + (2u << 20) - 1) & ~(uintptr_t)((2u << 20) - 1));
  cudaFuncSetAttribute(fused_kernel, cudaFuncAttributeMaxDynamicSharedMemorySize, SMEM_BYTES);
  cudaLaunchConfig_t cfg = {};
  cfg.gridDim = dim3(132); cfg.blockDim = dim3(384); cfg.dynamicSmemBytes = SMEM_BYTES; cfg.stream = cudaStreamPerThread;
  cudaLaunchAttribute at[1];
  at[0].id = cudaLaunchAttributeClusterDimension; at[0].val.clusterDim.x = 2; at[0].val.clusterDim.y = 1; at[0].val.clusterDim.z = 1;
  cfg.attrs = at; cfg.numAttrs = 1;
  int ncl = 0;
  cudaOccupancyMaxActiveClusters(&ncl, fused_kernel, &cfg);
  const bool last = ncl >= 66;
  for (int ci = 0; ci < 66; ci++) {
    const int tq = ci - 4;
    const int mp = (ci < 4 || ci >= 64) ? 0 : (tq < 32 ? tq & 7 : 1 + (tq - 32) % 7);
    const int j = ci < 4 ? (last ? 4 : 2) + ci : ci >= 64 ? ci - 58 : (tq < 32 ? tq >> 3 : 4 + (tq - 32) / 7);
    prm.role[ci] = (last ? ci >= 64 : ci < 2) ? 64 : mp | (j << 3);
  }
  cudaLaunchKernelEx(&cfg, fused_kernel, prm);
}
```
